```python
import torch

def _softmax(x, axis=-1):
    return torch.softmax(x, dim=axis)
def _gelu(x):
    return torch.nn.functional.gelu(x, approximate="tanh")
def _silu(x):
    return torch.nn.functional.silu(x)
def _sigmoid(x):
    return torch.sigmoid(x)
def _layernorm(x, axis=-1, eps=1e-5):
    m = x.mean(dim=axis, keepdim=True)
    v = x.var(dim=axis, keepdim=True, unbiased=False)
    return (x - m) / torch.sqrt(v + eps)
def _scatter_add(tgt, idx, src, axis=0):
    return tgt.clone().index_add_(axis, idx, src)
def _segment_sum(src, seg, n):
    out = torch.zeros((n,) + src.shape[1:], dtype=src.dtype)
    return out.index_add_(0, seg, src)
def _pad(x, pw):
    flat = tuple(v for pair in reversed(pw) for v in pair)
    return torch.nn.functional.pad(x, flat)

kernel_name = 'sequential_preLN__mha_block_cached__dense_activation_relu__decode'

def setup_inputs():

    _w = (lambda a: (lambda t: t.to(torch.bfloat16) if t.is_floating_point() else t)(torch.as_tensor(a)))
    def _A_setup():
        B, Sq, D = 2, 1, 640
        H, Sk, Dh = 32, 16384, 192
        return {
            "x": _w((lambda *s: torch.randn(*s, dtype=torch.bfloat16) * 0.05)(B, Sq, D)),
            "k_cache": _w((lambda *s: torch.randn(*s, dtype=torch.bfloat16) * 3.2)(B, H, Sk, Dh)),
            "v_cache": _w((lambda *s: torch.randn(*s, dtype=torch.bfloat16) * 0.4)(B, H, Sk, Dh)),
            "wq": _w((lambda *s: torch.randn(*s, dtype=torch.bfloat16) * 3.2)(D, H * Dh) * (D ** -0.5)),
            "wo": _w((lambda *s: torch.randn(*s, dtype=torch.bfloat16) * 0.4)(H * Dh, D) * ((H * Dh) ** -0.5)),
        }
    _A_in = _A_setup()

    def _B_setup():
        B, S, D, Dff = 2, 1, 640, 1536
        return {
            "x": _w((lambda *s: torch.randn(*s, dtype=torch.bfloat16) * 0.05)(B, S, D)),
            "w1": _w((lambda *s: torch.randn(*s, dtype=torch.bfloat16) * 0.05)(D, Dff)),
            "w2": _w((lambda *s: torch.randn(*s, dtype=torch.bfloat16) * 0.05)(Dff, D)),
        }
    _B_in = _B_setup()

    return {
        "A_x": _A_in["x"],
        "A_k_cache": _A_in["k_cache"],
        "A_v_cache": _A_in["v_cache"],
        "A_wq": _A_in["wq"],
        "A_wo": _A_in["wo"],
        "B_x": _B_in["x"],
        "B_w1": _B_in["w1"],
        "B_w2": _B_in["w2"],
    }

def reference(A_x, A_k_cache, A_v_cache, A_wq, A_wo, B_x, B_w1, B_w2):
    def _A_ref(x, k_cache, v_cache, wq, wo):
        B, Sq, D = x.shape
        H, Dh = 32, 192
        q = (lambda x, *d: x.permute(*d))((x @ wq).reshape(B, Sq, H, Dh), 0, 2, 1, 3)
        scores = torch.einsum("bhqd,bhkd->bhqk", q, k_cache) * (Dh ** -0.5)
        p = _softmax(scores, axis=-1)
        o = torch.einsum("bhqk,bhkd->bhqd", p, v_cache)
        return (lambda x, *d: x.permute(*d))(o, 0, 2, 1, 3).reshape(B, Sq, H * Dh) @ wo

    def _B_ref(x, w1, w2):
        h = torch.einsum("bsd,df->bsf", x, w1)
        zero = torch.zeros_like(h)
        h = torch.maximum(h, zero)
        return torch.einsum("bsf,fd->bsd", h, w2)

    x = A_x
    h = x + _A_ref(_layernorm(x, axis=-1), A_k_cache, A_v_cache, A_wq, A_wo)
    h2 = h + _B_ref(_layernorm(h, axis=-1), B_w1, B_w2)
    return h2
```

```cpp
#include <cuda_runtime.h>
#include <cuda_bf16.h>
#include <cuda.h>
#include <stdint.h>

namespace {

constexpr int DM = 640, NH = 32, SK = 16384, DH = 192, DFF = 1536, NBH = 64;
constexpr int KEYS = 64;
constexpr int IPB = SK / KEYS;
constexpr int NITEMS = NBH * IPB;
constexpr int NSTR = 64, NSVC = 64;
#define RING_NI 3
#define DONE_PAUSE 2000
#define REFRESH 0
#define KV_DELAY_NS 1500
constexpr int NI = RING_NI;
constexpr int TILE_BYTES = KEYS * DH * 2;
constexpr int NTHREADS = 512;
constexpr int NDYN = NITEMS - NI * NSTR;
constexpr unsigned TICKETS_PER_LAUNCH = NDYN + NSTR;
constexpr int PQ = 18;
constexpr int NFFN = 48;
constexpr int NRED = 32;
constexpr float LOG2E = 1.4426950408889634f;
constexpr float SCALE = 0.07216878364870322f;
constexpr uint32_t DESC_END = 0x7fffu;

constexpr int ST_RING = 0;
constexpr int ST_Q = NI * 2 * TILE_BYTES;
constexpr int NSC = 2;
constexpr int ST_SC = ST_Q + NBH * DH * 2;
constexpr int SC_STRIDE = 72;
constexpr int ST_BAR = ST_SC + NSC * SC_STRIDE * 4;
constexpr int ST_DESC = ST_BAR + (4 * NI + 2 * NSC) * 8;
constexpr int ST_QBAR = ST_DESC + 64;
constexpr int ST_END = ST_QBAR + NBH * 8;
constexpr int SV_R1 = 0;
constexpr int SV_W1 = 122880;
constexpr int SV_W2 = SV_W1 + 40960;
constexpr int SV_ACT = SV_W2 + 40960;
constexpr int ACT_STRIDE = 648;
constexpr int SV_X = SV_ACT + 2 * ACT_STRIDE * 2;
constexpr int SV_H = SV_X + 1280 * 4;
constexpr int SV_EARLY = SV_H + 640 * 4;
constexpr int SV_LATE = SV_EARLY + 640 * 4;
constexpr int SV_RED = SV_LATE + 640 * 4;
constexpr int SV_O = SV_RED + (16 * 48 + 32) * 4;
constexpr int SV_LN = SV_O + 128;
constexpr int SV_BAR = SV_LN + 128;
constexpr int SV_END = SV_BAR + 8 * 8;
constexpr int SMEM_BYTES = (ST_END > SV_END ? ST_END : SV_END) + 1024;
static_assert(SMEM_BYTES <= 232448 - 256, "smem");

struct Params {
    const __nv_bfloat16* x;
    __nv_bfloat16* out;
};

#define NREP 1
constexpr int NLATE = 4;
struct Scratch {
    unsigned epoch[32];
    unsigned ticket[32];
    unsigned done[NBH * 4];
    unsigned long long Q[NBH * 96];
    uint4 ES[256];
    uint4 LP[2][NLATE + NREP - 1][4][256];
    uint4 OP[NFFN][256];
    uint4 EP[NSVC + 16][256];
    uint4 P[NBH][NSTR][4][PQ];
};
__device__ __align__(128) Scratch g_scr;
#define TSCAL(k) do {} while (0)
#define TSD(i, dep) do {} while (0)
#define TS(i) do {} while (0)

__device__ __forceinline__ uint32_t smem_u32(const void* p) { return (uint32_t)__cvta_generic_to_shared(p); }
__device__ __forceinline__ void mbar_init(uint32_t bar, uint32_t cnt) { asm volatile("mbarrier.init.shared::cta.b64 [%0], %1;" ::"r"(bar), "r"(cnt)); }
__device__ __forceinline__ void mbar_expect_tx(uint32_t bar, uint32_t bytes) { asm volatile("mbarrier.arrive.expect_tx.shared::cta.b64 _, [%0], %1;" ::"r"(bar), "r"(bytes) : "memory"); }
__device__ __forceinline__ void mbar_arrive(uint32_t bar) { asm volatile("mbarrier.arrive.shared::cta.b64 _, [%0];" ::"r"(bar) : "memory"); }
__device__ __forceinline__ bool mbar_try(uint32_t bar, uint32_t parity) {
    uint32_t ok;
    asm volatile("{\n.reg .pred p;\nmbarrier.try_wait.parity.shared::cta.b64 p, [%1], %2;\nselp.u32 %0, 1, 0, p;\n}" : "=r"(ok) : "r"(bar), "r"(parity) : "memory");
    return ok != 0;
}
constexpr unsigned SPIN_LIMIT = 1u << 24;
__device__ __forceinline__ void mbar_wait(uint32_t bar, uint32_t parity) {
    unsigned n = 0;
    while (!mbar_try(bar, parity)) { if (++n > SPIN_LIMIT) __trap(); }
}
__device__ __forceinline__ void tma2d(uint32_t dst, const CUtensorMap* map, int c0, int c1, uint32_t bar) {
    asm volatile("cp.async.bulk.tensor.2d.shared::cluster.global.mbarrier::complete_tx::bytes [%0], [%1, {%3, %4}], [%2];"
                 ::"r"(dst), "l"(map), "r"(bar), "r"(c0), "r"(c1) : "memory");
}
__device__ __forceinline__ void tma2d_hint(uint32_t dst, const CUtensorMap* map, int c0, int c1, uint32_t bar, uint64_t pol) {
    asm volatile("cp.async.bulk.tensor.2d.shared::cluster.global.mbarrier::complete_tx::bytes.L2::cache_hint [%0], [%1, {%3, %4}], [%2], %5;"
                 ::"r"(dst), "l"(map), "r"(bar), "r"(c0), "r"(c1), "l"(pol) : "memory");
}
__device__ __forceinline__ void prefetch_map(const CUtensorMap* map) { asm volatile("prefetch.tensormap [%0];" ::"l"(map) : "memory"); }
__device__ __forceinline__ void ldsm4(uint32_t addr, uint32_t& r0, uint32_t& r1, uint32_t& r2, uint32_t& r3) {
    asm volatile("ldmatrix.sync.aligned.m8n8.x4.shared.b16 {%0,%1,%2,%3}, [%4];" : "=r"(r0), "=r"(r1), "=r"(r2), "=r"(r3) : "r"(addr));
}
__device__ __forceinline__ void ldsm4t(uint32_t addr, uint32_t& r0, uint32_t& r1, uint32_t& r2, uint32_t& r3) {
    asm volatile("ldmatrix.sync.aligned.m8n8.x4.trans.shared.b16 {%0,%1,%2,%3}, [%4];" : "=r"(r0), "=r"(r1), "=r"(r2), "=r"(r3) : "r"(addr));
}
__device__ __forceinline__ void mma16816(float (&d)[4], uint32_t a0, uint32_t a1, uint32_t a2, uint32_t a3, uint32_t b0, uint32_t b1) {
    asm volatile("mma.sync.aligned.m16n8k16.row.col.f32.bf16.bf16.f32 {%0,%1,%2,%3}, {%4,%5,%6,%7}, {%8,%9}, {%0,%1,%2,%3};"
                 : "+f"(d[0]), "+f"(d[1]), "+f"(d[2]), "+f"(d[3]) : "r"(a0), "r"(a1), "r"(a2), "r"(a3), "r"(b0), "r"(b1));
}
__device__ __forceinline__ float ex2(float x) { float y; asm("ex2.approx.ftz.f32 %0, %1;" : "=f"(y) : "f"(x)); return y; }
__device__ __forceinline__ uint32_t pack_bf16(float lo, float hi) {
    uint32_t r; asm("cvt.rn.bf16x2.f32 %0, %1, %2;" : "=r"(r) : "f"(hi), "f"(lo)); return r;
}
__device__ __forceinline__ float bf16r(float x) { return __uint_as_float(pack_bf16(0.f, x) & 0xffff0000u); }
__device__ __forceinline__ void st_pkt(unsigned long long* p, uint32_t payload, uint32_t tag) {
    unsigned long long v = ((unsigned long long)tag << 32) | payload;
    asm volatile("st.relaxed.gpu.global.b64 [%0], %1;" ::"l"(p), "l"(v) : "memory");
}
__device__ __forceinline__ unsigned long long ld_pkt(const unsigned long long* p) {
    unsigned long long v; asm volatile("ld.relaxed.gpu.global.b64 %0, [%1];" : "=l"(v) : "l"(p) : "memory"); return v;
}
__device__ __forceinline__ uint32_t pkt_tag(unsigned long long v) { return (uint32_t)(v >> 32); }
__device__ __forceinline__ void st_pkt4(uint4* p, uint32_t a, uint32_t b, uint32_t c, uint32_t tag) {
    asm volatile("{\n.reg .b64 lo, hi;\n.reg .b128 t;\nmov.b64 lo, {%1, %2};\nmov.b64 hi, {%3, %4};\nmov.b128 t, {lo, hi};\nst.relaxed.gpu.global.b128 [%0], t;\n}"
                 ::"l"(p), "r"(a), "r"(b), "r"(c), "r"(tag) : "memory");
}
__device__ __forceinline__ void st_pkt4f(uint4* p, float a, float b, float c, uint32_t tag) { st_pkt4(p, __float_as_uint(a), __float_as_uint(b), __float_as_uint(c), tag); }
__device__ __forceinline__ uint4 ld_pkt4(const uint4* p) {
    uint4 v;
    asm volatile("{\n.reg .b64 lo, hi;\n.reg .b128 t;\nld.relaxed.gpu.global.b128 t, [%4];\nmov.b128 {lo, hi}, t;\nmov.b64 {%0, %1}, lo;\nmov.b64 {%2, %3}, hi;\n}"
                 : "=r"(v.x), "=r"(v.y), "=r"(v.z), "=r"(v.w) : "l"(p) : "memory");
    return v;
}
__device__ __forceinline__ unsigned ld_relaxed_u32(const unsigned* p) {
    unsigned v; asm volatile("ld.relaxed.gpu.global.u32 %0, [%1];" : "=r"(v) : "l"(p) : "memory"); return v;
}
__device__ __forceinline__ void pause_cycles(int cyc) {
    const long long t0 = clock64();
    while (clock64() - t0 < cyc) {}
}
__device__ __forceinline__ void touch(const void* p) { asm volatile("prefetch.global.L2 [%0];" ::"l"(p) : "memory"); }
__device__ __forceinline__ void red_add_u32(unsigned* p, unsigned v) { asm volatile("red.relaxed.gpu.global.add.u32 [%0], %1;" ::"l"(p), "r"(v) : "memory"); }
__device__ __forceinline__ void spin_check(unsigned& n) { if (++n > SPIN_LIMIT) __trap(); }
__device__ __forceinline__ unsigned long long globaltimer() { unsigned long long t; asm volatile("mov.u64 %0, %globaltimer;" : "=l"(t)); return t; }
__device__ __forceinline__ int opaque(int v) { asm volatile("" : "+r"(v)); return v; }

__device__ __forceinline__ void streamer(uint8_t* smem, Scratch* scr, const CUtensorMap* mk, const CUtensorMap* mv, int j, unsigned epoch, unsigned long long t_start) {
    const int warp = threadIdx.x >> 5, lane = threadIdx.x & 31;
    const uint32_t sbase = smem_u32(smem);
    const uint32_t bar0 = sbase + ST_BAR;
    volatile uint32_t* desc = reinterpret_cast<volatile uint32_t*>(smem + ST_DESC);
    auto fullK = [&](int s) { return bar0 + 8 * s; };
    auto fullV = [&](int s) { return bar0 + 8 * (NI + s); };
    auto emptyK = [&](int s) { return bar0 + 8 * (2 * NI + s); };
    auto emptyV = [&](int s) { return bar0 + 8 * (3 * NI + s); };
    const uint32_t tag = 2 * epoch + 1;

    auto scFull = [&](int b) { return bar0 + 8 * (4 * NI + b); };
    auto scEmpty = [&](int b) { return bar0 + 8 * (4 * NI + NSC + b); };
    float* sc = reinterpret_cast<float*>(smem + ST_SC);
    const int g = lane >> 2, c = lane & 3, mat = lane >> 3, r8 = lane & 7;

    if (warp == 8) {
        if (lane == 0) {
            uint64_t pol;
            asm volatile("createpolicy.fractional.L2::evict_first.b64 %0, 1.0;" : "=l"(pol));
            int s = 0; uint32_t ph = 1;
            auto issue = [&](unsigned item) {
                mbar_wait(emptyK(s), ph);
                desc[s] = item;
                mbar_expect_tx(fullK(s), TILE_BYTES);
                tma2d_hint(sbase + ST_RING + s * 2 * TILE_BYTES, mk, 0, (int)item * (KEYS * 3), fullK(s), pol);
                mbar_wait(emptyV(s), ph);
                mbar_expect_tx(fullV(s), TILE_BYTES);
                tma2d_hint(sbase + ST_RING + s * 2 * TILE_BYTES + TILE_BYTES, mv, 0, (int)item * (KEYS * 3), fullV(s), pol);
                if (++s == NI) { s = 0; ph ^= 1; }
            };
            if (KV_DELAY_NS > 0) {
                while (globaltimer() - t_start < KV_DELAY_NS) {}
            }
            TS(4);
            issue(j);
            unsigned d0 = atomicAdd(&scr->ticket[0], 1u);
            mbar_wait(sbase + ST_QBAR, 0);
#pragma unroll 1
            for (int i = 1; i < NI; i++) issue(j + NSTR * i);
            const unsigned base = epoch * TICKETS_PER_LAUNCH;
            while (true) {
                const unsigned c0 = d0 - base;
                if (c0 >= (unsigned)NDYN) break;
                d0 = atomicAdd(&scr->ticket[0], 1u);
                issue(c0 + NI * NSTR);
            }
            mbar_wait(emptyK(s), ph);
            desc[s] = DESC_END;
            mbar_arrive(fullK(s));
            TS(1);
        }
    } else if (warp == 9) {
        uint32_t* qs = reinterpret_cast<uint32_t*>(smem + ST_Q);
        for (int bh = 0; bh < NBH; bh++) {
            unsigned long long v0, v1, v2; unsigned n = 0;
            while (true) {
                v0 = ld_pkt(&scr->Q[bh * 96 + lane]); v1 = ld_pkt(&scr->Q[bh * 96 + 32 + lane]); v2 = ld_pkt(&scr->Q[bh * 96 + 64 + lane]);
                bool ok = pkt_tag(v0) == tag && pkt_tag(v1) == tag && pkt_tag(v2) == tag;
                if (__all_sync(0xffffffffu, ok)) break;
                spin_check(n);
            }
            qs[bh * 96 + lane] = (uint32_t)v0; qs[bh * 96 + 32 + lane] = (uint32_t)v1; qs[bh * 96 + 64 + lane] = (uint32_t)v2;
            __syncwarp();
            if (lane == 0) mbar_arrive(sbase + ST_QBAR + 8 * bh);
            if (bh == 0 && lane == 0) TS(2);
        }
    } else if (warp >= 4 && warp < 8) {
        const int w4 = warp - 4;
        uint32_t koff[3];
        {
            int key = 16 * w4 + (mat & 1) * 8 + r8;
#pragma unroll
            for (int sg = 0; sg < 3; sg++) { int row = 3 * key + sg; koff[sg] = row * 128 + (((mat >> 1) ^ (row & 7)) << 4); }
        }
        const uint32_t* qs = reinterpret_cast<const uint32_t*>(smem + ST_Q);
        uint32_t qa[24];
        int cur_bh = -1;
        int s = 0; uint32_t ph = 0; int par = 0; uint32_t sph = 1;
        bool dry = opaque(1) != 0;
        while (true) {
            uint32_t d = 0;
            if (!dry) { mbar_wait(fullK(s), ph); d = desc[s]; }
            float* scb = sc + par * SC_STRIDE;
            if (d == DESC_END) {
                mbar_wait(scEmpty(par), sph);
                if (lane == 0) { if (w4 == 0) reinterpret_cast<uint32_t*>(scb)[64] = d; mbar_arrive(scFull(par)); }
                break;
            }
            const int bh = (d & 0x7fffu) / IPB;
            if (bh != cur_bh) {
                cur_bh = bh;
                if (!dry) mbar_wait(sbase + ST_QBAR + 8 * bh, 0);
#pragma unroll
                for (int jj = 0; jj < 12; jj++) { qa[2 * jj] = qs[bh * 96 + 8 * jj + c]; qa[2 * jj + 1] = qs[bh * 96 + 8 * jj + 4 + c]; }
            }
            const uint32_t kb = sbase + ST_RING + s * 2 * TILE_BYTES;
            float sa[3][4];
            {
                uint32_t kf[12][4];
#pragma unroll
                for (int jj = 0; jj < 12; jj++) ldsm4(kb + (koff[jj >> 2] ^ ((jj & 3) << 5)), kf[jj][0], kf[jj][1], kf[jj][2], kf[jj][3]);
#pragma unroll
                for (int sg = 0; sg < 3; sg++) { sa[sg][0] = sa[sg][1] = sa[sg][2] = sa[sg][3] = 0.f; }
#pragma unroll
                for (int i = 0; i < 4; i++)
#pragma unroll
                    for (int sg = 0; sg < 3; sg++) {
                        const int jj = 4 * sg + i;
                        mma16816(sa[sg], kf[jj][0], kf[jj][1], kf[jj][2], kf[jj][3], qa[2 * jj], qa[2 * jj + 1]);
                    }
            }
            const float r0 = (sa[0][0] + sa[1][0]) + sa[2][0], r1 = (sa[0][2] + sa[1][2]) + sa[2][2];
            const float v = bf16r(bf16r(c == 0 ? r0 : r1) * SCALE);
            __syncwarp();
            if (dry) { dry = false; cur_bh = -1; continue; }
            if (lane == 0) mbar_arrive(emptyK(s));
            mbar_wait(scEmpty(par), sph);
            if (c < 2) scb[16 * w4 + g + 8 * c] = v;
            if (w4 == 0 && lane == 2) reinterpret_cast<uint32_t*>(scb)[64] = d;
            __syncwarp();
            if (lane == 0) mbar_arrive(scFull(par));
            if (++par == NSC) { par = 0; sph ^= 1; }
            if (++s == NI) { s = 0; ph ^= 1; }
        }
    } else if (warp < 4) {
        uint32_t voff[3];
        {
            int key = (mat >> 1) * 8 + r8;
#pragma unroll
            for (int t = 0; t < 3; t++) { int cj = 6 * warp + 2 * t + (mat & 1); int row = 3 * key + (cj >> 3); voff[t] = row * 128 + (((cj & 7) ^ (row & 7)) << 4); }
        }
        float o[3][4];
#pragma unroll
        for (int t = 0; t < 3; t++) { o[t][0] = o[t][1] = o[t][2] = o[t][3] = 0.f; }
        float m = -INFINITY, l = 0.f, lt = 0.f;
        int cur_bh = 0, nit = 0;
        int s = 0; uint32_t ph = 0; int par = 0; uint32_t sph = 0;
        bool dry = opaque(1) != 0;
        while (true) {
            const float* scb = sc + par * SC_STRIDE;
            if (!dry) mbar_wait(scFull(par), sph);
            const float2 sv = *reinterpret_cast<const float2*>(scb + 2 * lane);
            uint32_t d = reinterpret_cast<const uint32_t*>(scb)[64];
            if (dry) d = IPB;
            __syncwarp();
            if (lane == 0 && !dry) mbar_arrive(scEmpty(par));
            const int bh = d == DESC_END ? NBH : (int)(d / IPB);
            if (bh != cur_bh) {
                if (!dry) {
                    uint4* P = scr->P[cur_bh][j][warp];
                    const int x = c == 1 ? 2 : 0;
                    const uint32_t pa = c < 2 ? __float_as_uint(c == 1 ? o[0][2] : o[0][0]) : ((__float_as_uint(m) & 0xffff0000u) | (uint32_t)nit);
                    const uint32_t pb2 = c < 2 ? __float_as_uint(c == 1 ? o[1][2] : o[1][0]) : __float_as_uint(lt);
                    const uint32_t pc = __float_as_uint(c == 1 ? o[2][2] : o[2][0]);
                    (void)x;
                    if (c < 2 || (c == 2 && g < 2)) st_pkt4(P + (c < 2 ? 2 + 8 * c + g : g), pa, pb2, pc, tag);
                    if (lane == 0) red_add_u32(&scr->done[cur_bh * 4 + warp], (unsigned)nit);
#pragma unroll 1
                    for (int e = cur_bh + 1; e < bh; e++)
                        if (c == 2 && g < 2) st_pkt4(scr->P[e][j][warp] + g, 0xff800000u, 0u, 0u, tag);
                }
                if (d == DESC_END) break;
                cur_bh = bh; nit = 0; m = -INFINITY; l = 0.f;
#pragma unroll
                for (int t = 0; t < 3; t++) { o[t][0] = o[t][1] = o[t][2] = o[t][3] = 0.f; }
            }
            nit++;
            int key = __float_as_int(fmaxf(sv.x, sv.y));
            key ^= (key >> 31) & 0x7fffffff;
            key = __reduce_max_sync(0xffffffffu, key);
            key ^= (key >> 31) & 0x7fffffff;
            const float mn = fmaxf(m, __int_as_float(key));
            const float mb = mn * LOG2E;
            const float p0 = ex2(fmaf(sv.x, LOG2E, -mb)), p1 = ex2(fmaf(sv.y, LOG2E, -mb));
            const float alpha = ex2((m - mn) * LOG2E);
            m = mn;
            const uint32_t pk = pack_bf16(p0, p1);
            uint32_t pb[8];
#pragma unroll
            for (int i = 0; i < 8; i++) pb[i] = __shfl_sync(0xffffffffu, pk, 4 * i + c);
            l = fmaf(l, alpha, p0 + p1);
            lt = l;
#pragma unroll
            for (int off = 1; off < 32; off <<= 1) lt += __shfl_xor_sync(0xffffffffu, lt, off);
#pragma unroll
            for (int t = 0; t < 3; t++) { o[t][0] *= alpha; o[t][2] *= alpha; }
            if (!dry) mbar_wait(fullV(s), ph);
            const uint32_t vb = sbase + ST_RING + s * 2 * TILE_BYTES + TILE_BYTES;
            {
                uint32_t vf[12][4];
#pragma unroll
                for (int kk = 0; kk < 4; kk++)
#pragma unroll
                    for (int t = 0; t < 3; t++) ldsm4t(vb + voff[t] + kk * 6144, vf[3 * kk + t][0], vf[3 * kk + t][1], vf[3 * kk + t][2], vf[3 * kk + t][3]);
#pragma unroll
                for (int kk = 0; kk < 4; kk++)
#pragma unroll
                    for (int t = 0; t < 3; t++) mma16816(o[t], vf[3 * kk + t][0], vf[3 * kk + t][1], vf[3 * kk + t][2], vf[3 * kk + t][3], pb[2 * kk], pb[2 * kk + 1]);
            }
            __syncwarp();
            if (dry) {
                dry = false; cur_bh = 0; nit = 0; m = -INFINITY; l = 0.f;
#pragma unroll
                for (int t = 0; t < 3; t++) { o[t][0] = o[t][1] = o[t][2] = o[t][3] = 0.f; }
                continue;
            }
            if (lane == 0) mbar_arrive(emptyV(s));
            if (++par == NSC) { par = 0; sph ^= 1; }
            if (++s == NI) { s = 0; ph ^= 1; }
        }
        if (threadIdx.x == 0) TS(3);
    }
}

__device__ __noinline__ void block_ln(uint8_t* smem, bool active, float v0, float v1, float v2) {
    const int tid = threadIdx.x, warp = tid >> 5, lane = tid & 31;
    const int grp = warp >> 3, w8 = warp & 7, p = tid & 255;
    const bool has3 = w8 < 4;
    float* lnb = reinterpret_cast<float*>(smem + SV_LN) + grp * 16;
    if (active) {
        float mean = has3 ? ((v0 + v1) + v2) * (1.f / 3.f) : (v0 + v1) * 0.5f;
        const float d0 = v0 - mean, d1 = v1 - mean, d2 = has3 ? v2 - mean : 0.f;
        float m2 = d0 * d0 + d1 * d1 + d2 * d2;
        float cnt_half = has3 ? 1.5f : 1.f;
#pragma unroll
        for (int off = 1; off < 32; off <<= 1) {
            const float mo = __shfl_xor_sync(0xffffffffu, mean, off), m2o = __shfl_xor_sync(0xffffffffu, m2, off);
            const float dl = mo - mean;
            m2 = m2 + m2o + dl * dl * cnt_half;
            mean = 0.5f * (mean + mo);
            cnt_half *= 2.f;
        }
        if (lane == 0) *reinterpret_cast<float2*>(lnb + w8 * 2) = make_float2(mean, m2);
    }
    __syncthreads();
    if (active) {
        const float4 a = *reinterpret_cast<const float4*>(lnb), b = *reinterpret_cast<const float4*>(lnb + 4);
        const float4 c = *reinterpret_cast<const float4*>(lnb + 8), d = *reinterpret_cast<const float4*>(lnb + 12);
        const float mean = ((a.x + a.z) + (b.x + b.z)) * 0.15f + ((c.x + c.z) + (d.x + d.z)) * 0.1f;
        const float e0 = a.x - mean, e1 = a.z - mean, e2 = b.x - mean, e3 = b.z - mean, e4 = c.x - mean, e5 = c.z - mean, e6 = d.x - mean, e7 = d.z - mean;
        const float m2 = ((a.y + a.w) + (b.y + b.w)) + ((c.y + c.w) + (d.y + d.w)) + 96.f * ((e0 * e0 + e1 * e1) + (e2 * e2 + e3 * e3)) + 64.f * ((e4 * e4 + e5 * e5) + (e6 * e6 + e7 * e7));
        const float mr = bf16r(mean), vr = bf16r(m2 * (1.f / 640.f));
        const float den = bf16r(__fsqrt_rn(bf16r(vr + 1e-5f)));
        __nv_bfloat16* act = reinterpret_cast<__nv_bfloat16*>(smem + SV_ACT) + grp * ACT_STRIDE;
        act[p] = __float2bfloat16_rn(__fdividef(bf16r(v0 - mr), den));
        act[p + 256] = __float2bfloat16_rn(__fdividef(bf16r(v1 - mr), den));
        if (has3) act[p + 512] = __float2bfloat16_rn(__fdividef(bf16r(v2 - mr), den));
    }
    __syncthreads();
}

__device__ __forceinline__ void combine(uint8_t* smem, const Scratch* scr, int bh, int qt, uint32_t tag) {
    const int tid = threadIdx.x, warp = tid >> 5, lane = tid & 31;
    const int jrow = 4 * warp + (lane >> 3), pg = lane & 7;
    const uint4* rp = scr->P[bh][jrow][qt];
    uint4 hd = make_uint4(0, 0, 0, 0), d0 = hd, d1 = hd;
    bool nonempty = false, ok = false;
    unsigned n = 0;
    while (true) {
        if (!ok) {
            hd = ld_pkt4(rp); d0 = ld_pkt4(rp + 2 + pg); d1 = ld_pkt4(rp + 10 + pg);
            nonempty = (hd.x & 0xffffu) != 0;
            ok = hd.w == tag && (!nonempty || (d0.w == tag && d1.w == tag));
        }
        if (__all_sync(0xffffffffu, ok)) break;
        spin_check(n);
    }
    if (tid == 0 && bh == 63) TS(14);
    const float mj = __uint_as_float(hd.x & 0xffff0000u);
    float M = mj;
    M = fmaxf(M, __shfl_xor_sync(0xffffffffu, M, 8));
    M = fmaxf(M, __shfl_xor_sync(0xffffffffu, M, 16));
    const float wj = nonempty ? ex2((mj - M) * LOG2E) : 0.f;
    float val[7];
    val[0] = nonempty ? __uint_as_float(d0.x) * wj : 0.f; val[1] = nonempty ? __uint_as_float(d0.y) * wj : 0.f; val[2] = nonempty ? __uint_as_float(d0.z) * wj : 0.f;
    val[3] = nonempty ? __uint_as_float(d1.x) * wj : 0.f; val[4] = nonempty ? __uint_as_float(d1.y) * wj : 0.f; val[5] = nonempty ? __uint_as_float(d1.z) * wj : 0.f;
    val[6] = nonempty ? __uint_as_float(hd.y) * wj : 0.f;
#pragma unroll
    for (int i = 0; i < 7; i++) { val[i] += __shfl_xor_sync(0xffffffffu, val[i], 8); val[i] += __shfl_xor_sync(0xffffffffu, val[i], 16); }
    float* red = reinterpret_cast<float*>(smem + SV_RED);
    if (lane < 8) {
#pragma unroll
        for (int i = 0; i < 3; i++) { red[warp * 48 + 16 * i + pg] = val[i]; red[warp * 48 + 16 * i + 8 + pg] = val[3 + i]; }
        if (lane == 0) { red[768 + warp] = M; red[784 + warp] = val[6]; }
    }
    __syncthreads();
    if (tid == 0 && bh == 63) TS(15);
    if (tid < 64) {
        const float Mw = red[768 + (lane & 15)];
        int key = __float_as_int(Mw);
        key ^= (key >> 31) & 0x7fffffff;
        key = __reduce_max_sync(0xffffffffu, key);
        key ^= (key >> 31) & 0x7fffffff;
        const float scw = Mw == -INFINITY ? 0.f : ex2((Mw - __int_as_float(key)) * LOG2E);
        const int dd = tid < 48 ? tid : 0;
        float a0 = 0.f, a1 = 0.f, l0 = 0.f, l1 = 0.f;
#pragma unroll
        for (int w = 0; w < 16; w += 2) {
            const float s0 = __shfl_sync(0xffffffffu, scw, w), s1 = __shfl_sync(0xffffffffu, scw, w + 1);
            a0 = fmaf(s0, red[w * 48 + dd], a0); a1 = fmaf(s1, red[(w + 1) * 48 + dd], a1);
            l0 = fmaf(s0, red[784 + w], l0); l1 = fmaf(s1, red[784 + w + 1], l1);
        }
        if (tid < 48) reinterpret_cast<__nv_bfloat16*>(smem + SV_O)[tid] = __float2bfloat16_rn(__fdividef(a0 + a1, l0 + l1));
    }
    __syncthreads();
}

__device__ __forceinline__ void wo_load(uint8_t* smem, int slice, uint32_t (&af)[9][4]) {
    const int warp = threadIdx.x >> 5, lane = threadIdx.x & 31;
    const int mat = lane >> 3, r8 = lane & 7;
    const uint32_t base = smem_u32(smem) + SV_R1 + slice * 61440;
#pragma unroll
    for (int kk = 0; kk < 3; kk++) {
        const int row = 16 * kk + (mat >> 1) * 8 + r8;
#pragma unroll
        for (int i = 0; i < 3; i++) {
            const int t = min(warp + 16 * i, 39);
            ldsm4t(base + (t >> 2) * 6144 + row * 128 + (((((t & 3) << 1) + (mat & 1)) ^ (row & 7)) << 4), af[3 * kk + i][0], af[3 * kk + i][1], af[3 * kk + i][2], af[3 * kk + i][3]);
        }
    }
}
__device__ __forceinline__ void wo_mma(uint8_t* smem, const uint32_t (&af)[9][4], float (&acc)[3][4]) {
    const int c = threadIdx.x & 3;
    const uint32_t* ow = reinterpret_cast<const uint32_t*>(smem + SV_O);
    uint32_t bf[6];
#pragma unroll
    for (int kk = 0; kk < 3; kk++) { bf[2 * kk] = ow[8 * kk + c]; bf[2 * kk + 1] = ow[8 * kk + 4 + c]; }
#pragma unroll
    for (int kk = 0; kk < 3; kk++)
#pragma unroll
        for (int i = 0; i < 3; i++) mma16816(acc[i], af[3 * kk + i][0], af[3 * kk + i][1], af[3 * kk + i][2], af[3 * kk + i][3], bf[2 * kk], bf[2 * kk + 1]);
}
__device__ __forceinline__ void publish640(uint4* dst, const float (&acc)[3][4], uint32_t tag) {
    const int warp = threadIdx.x >> 5, lane = threadIdx.x & 31, g = lane >> 2, c = lane & 3;
    if (c < 2) st_pkt4f(dst + 16 * warp + 8 * c + g, c ? acc[0][2] : acc[0][0], c ? acc[1][2] : acc[1][0], c ? acc[2][2] : acc[2][0], tag);
}

template <int NPROD>
__device__ __forceinline__ void gather8(uint8_t* smem, const uint4* src, uint32_t tag) {
    const int tid = threadIdx.x, warp = tid >> 5, lane = tid & 31;
    float x0 = 0.f, x1 = 0.f, x2 = 0.f;
    if (tid < NPROD * 8) {
        uint4 v; unsigned n = 0;
        while (true) { v = ld_pkt4(src); if (v.w == tag) break; spin_check(n); }
        x0 = __uint_as_float(v.x); x1 = __uint_as_float(v.y); x2 = __uint_as_float(v.z);
    }
    x0 += __shfl_xor_sync(0xffffffffu, x0, 8); x1 += __shfl_xor_sync(0xffffffffu, x1, 8); x2 += __shfl_xor_sync(0xffffffffu, x2, 8);
    x0 += __shfl_xor_sync(0xffffffffu, x0, 16); x1 += __shfl_xor_sync(0xffffffffu, x1, 16); x2 += __shfl_xor_sync(0xffffffffu, x2, 16);
    float* red = reinterpret_cast<float*>(smem + SV_RED);
    if (lane < 8) { red[warp * 24 + lane] = x0; red[warp * 24 + 8 + lane] = x1; red[warp * 24 + 16 + lane] = x2; }
    __syncthreads();
}

__device__ __forceinline__ void service(uint8_t* smem, Scratch* scr, __nv_bfloat16* outp, const CUtensorMap* mo, int s, unsigned epoch,
                                        uint32_t xr0, uint32_t xr1, uint32_t xr2) {
    const int tid = threadIdx.x, warp = tid >> 5, lane = tid & 31;
    const int g = lane >> 2, c = lane & 3, mat = lane >> 3, r8 = lane & 7;
    const uint32_t sbase = smem_u32(smem);
    const uint32_t bar_wq = sbase + SV_BAR, bar_wo = bar_wq + 32, bar_w12 = bar_wq + 40;
    const uint32_t tag = 2 * epoch + 1;
    float* xs = reinterpret_cast<float*>(smem + SV_X);
    float* hs = reinterpret_cast<float*>(smem + SV_H);
    float* early = reinterpret_cast<float*>(smem + SV_EARLY);
    float* lates = reinterpret_cast<float*>(smem + SV_LATE);
    float* red = reinterpret_cast<float*>(smem + SV_RED);
    const uint32_t* actw = reinterpret_cast<const uint32_t*>(smem + SV_ACT);
    const int h0 = s >> 2, qt = s & 3;
    const bool late_owner = (h0 >= 16 - NLATE);

    {
        const float v0 = __uint_as_float(xr0 << 16), v1 = __uint_as_float(xr1 << 16), v2 = __uint_as_float(xr2 << 16);
        const int b = tid >> 8, p = tid & 255;
        xs[b * 640 + p] = v0; xs[b * 640 + p + 256] = v1;
        if (p < 128) xs[b * 640 + p + 512] = v2;
        if (tid == 0) TS(8);
        block_ln(smem, true, v0, v1, v2);
        if (tid == 0) TS(9);
    }
    {
        float acc[4] = {0, 0, 0, 0};
        const int mt = warp % 6, kp = warp / 6;
        if (warp < 12) {
#pragma unroll 1
            for (int rc = 0; rc < 4; rc++) {
                mbar_wait(bar_wq + 8 * rc, 0);
                if (tid == 0) TS(10 + rc);
#pragma unroll
                for (int i = 0; i < 5; i++) {
                    const int ks = rc * 10 + 2 * i + kp;
                    const int row = 16 * ks + (mat >> 1) * 8 + r8;
                    const int ch = ((mt & 1) << 1) + (mat & 1);
                    uint32_t a0, a1, a2, a3;
                    ldsm4t(sbase + SV_R1 + (mt >> 1) * 40960 + row * 64 + ((ch ^ ((row >> 1) & 3)) << 4), a0, a1, a2, a3);
                    const uint32_t b0 = actw[(g & 1) * (ACT_STRIDE / 2) + 8 * ks + c], b1 = actw[(g & 1) * (ACT_STRIDE / 2) + 8 * ks + 4 + c];
                    mma16816(acc, a0, a1, a2, a3, b0, b1);
                }
            }
            if (c == 0) {
                *reinterpret_cast<float2*>(red + (kp * 96 + 16 * mt + g) * 2) = make_float2(acc[0], acc[1]);
                *reinterpret_cast<float2*>(red + (kp * 96 + 16 * mt + g + 8) * 2) = make_float2(acc[2], acc[3]);
            }
        }
        __syncthreads();
        if (tid < 96) {
            const int b = tid / 48, pi = tid % 48;
            const float q0 = red[(2 * pi) * 2 + b] + red[(96 + 2 * pi) * 2 + b];
            const float q1 = red[(2 * pi + 1) * 2 + b] + red[(96 + 2 * pi + 1) * 2 + b];
            st_pkt(&scr->Q[(b * 32 + (s >> 1)) * 96 + (s & 1) * 48 + pi], pack_bf16(q0, q1), tag);
        }
        if (tid == 128) {
            TS(1);
            asm volatile("fence.proxy.async.shared::cta;" ::: "memory");
            mbar_expect_tx(bar_wo, 122880);
#pragma unroll 1
            for (int i = 0; i < 20; i++) {
                const int sl = i / 10, nb = i % 10;
                tma2d(sbase + SV_R1 + sl * 61440 + nb * 6144, mo, 64 * nb, (h0 + 16 * sl) * DH + qt * 48, bar_wo);
            }
        }
        __syncthreads();
    }
    const unsigned tbase = epoch * TICKETS_PER_LAUNCH;
    auto wait_handed_out = [&](int bh) {
        if (tid == 0) {
            const int need = (bh + 1) * IPB - NI * NSTR;
            unsigned n = 0;
            while ((int)(ld_relaxed_u32(&scr->ticket[0]) - tbase) < need) { pause_cycles(600); spin_check(n); }
        }
        __syncthreads();
    };
    mbar_wait(bar_wo, 0);

#pragma unroll 1
    for (int b = 0; b < 2; b++) {
        const uint32_t rtag = tag + b;
        float acc[3][4];
#pragma unroll
        for (int i = 0; i < 3; i++) acc[i][0] = acc[i][1] = acc[i][2] = acc[i][3] = 0.f;
#pragma unroll 1
        for (int task = 0; task < 2; task++) {
            const int bh = 32 * b + h0 + 16 * task;
            if (task == 1 && late_owner) {
                publish640(scr->EP[b == 0 ? s : s + 16], acc, rtag);
#pragma unroll
                for (int i = 0; i < 3; i++) acc[i][0] = acc[i][1] = acc[i][2] = acc[i][3] = 0.f;
            }
            uint32_t af[9][4];
            wo_load(smem, task, af);
            if (bh < 62) {
                if (tid == 0) {
                    const unsigned target = (epoch + 1) * IPB;
                    unsigned n = 0;
                    while ((int)(ld_relaxed_u32(&scr->done[bh * 4 + qt]) - target) < 0) { pause_cycles(600); spin_check(n); }
                    pause_cycles(DONE_PAUSE);
                }
                __syncthreads();
            } else {
                wait_handed_out(bh);
                if (REFRESH && c < 2) st_pkt4(&scr->LP[1][bh - (NBH - NLATE)][qt][16 * warp + 8 * c + g], 0u, 0u, 0u, 0u);
            }
            if (tid == 0 && b == 1 && task == 1) TS(20);
            combine(smem, scr, bh, qt, tag);
            if (tid == 0 && b == 1 && task == 1) TS(21);
            wo_mma(smem, af, acc);
            if (tid == 0 && b == 1 && task == 1) TSD(6, acc[0][0] + acc[1][0] + acc[2][0]);
        }
        if (late_owner) {
            publish640(scr->LP[b][h0 - (16 - NLATE)][qt], acc, rtag);
            if (h0 == 15) {
#pragma unroll
                for (int r = 1; r < NREP; r++) publish640(scr->LP[b][NLATE - 1 + r][qt], acc, rtag);
            }
            if (tid == 0) TS(22);
            continue;
        }
        publish640(scr->EP[s], acc, rtag);
        if (tid == 0) TS(22);
        wait_handed_out(32 * b + 32 - NLATE);
        if (s < NRED) {
            const int prod = tid >> 3;
            gather8<NSVC>(smem, &scr->EP[(prod >= NFFN && b == 1) ? prod + 16 : prod][8 * s + (tid & 7)], rtag);
            if (tid < 8) {
                float y0 = 0.f, y1 = 0.f, y2 = 0.f;
#pragma unroll
                for (int w = 0; w < 16; w++) { y0 += red[w * 24 + tid]; y1 += red[w * 24 + 8 + tid]; y2 += red[w * 24 + 16 + tid]; }
                st_pkt4f(&scr->ES[8 * s + tid], y0, y1, y2, rtag);
            }
            if (tid == 0) TS(23);
        }
        if (tid < 256) {
            uint4 v; unsigned n = 0;
            while (true) { v = ld_pkt4(&scr->ES[tid]); if (v.w == rtag) break; spin_check(n); pause_cycles(100); }
            early[tid] = __uint_as_float(v.x); early[tid + 256] = __uint_as_float(v.y);
            if (tid < 128) early[tid + 512] = __uint_as_float(v.z);
        }
        mbar_wait(bar_w12, 0);
        if (REFRESH && b == 1 && c < 2) st_pkt4(&scr->OP[s][16 * warp + 8 * c + g], 0u, 0u, 0u, 0u);
        uint32_t w1f[5][4], w2f[6][4];
        {
            const int mt = warp & 1, kg = warp >> 1;
#pragma unroll
            for (int i = 0; i < 5; i++) {
                const int row = 16 * (kg * 5 + i) + (mat >> 1) * 8 + r8;
                const int ch = (mt << 1) + (mat & 1);
                ldsm4t(sbase + SV_W1 + row * 64 + ((ch ^ ((row >> 1) & 3)) << 4), w1f[i][0], w1f[i][1], w1f[i][2], w1f[i][3]);
            }
#pragma unroll
            for (int kk = 0; kk < 2; kk++) {
                const int row = 16 * kk + (mat >> 1) * 8 + r8;
#pragma unroll
                for (int i = 0; i < 3; i++) {
                    const int t = min(warp + 16 * i, 39);
                    ldsm4t(sbase + SV_W2 + (t >> 2) * 4096 + row * 128 + (((((t & 3) << 1) + (mat & 1)) ^ (row & 7)) << 4), w2f[3 * kk + i][0], w2f[3 * kk + i][1], w2f[3 * kk + i][2], w2f[3 * kk + i][3]);
                }
            }
        }
        if (tid == 0) TS(2);
        {
            float v0 = 0.f, v1 = 0.f, v2 = 0.f;
            const int grp = warp >> 3, p = tid & 255;
            float e0 = 0.f, e1 = 0.f, e2 = 0.f;
            const int lh_lo = grp ? 0 : NLATE - 1, lh_hi = grp ? NLATE - 1 : NLATE;
#pragma unroll 1
            for (int lh = lh_lo; lh < lh_hi; lh++) {
                if (p == 0) {
                    unsigned n2 = 0;
                    if (lh < NLATE - 1 || b == 0) {
                        while (true) {
                            const uint32_t g0 = ld_pkt4(&scr->LP[b][lh][0][0]).w, g1 = ld_pkt4(&scr->LP[b][lh][1][0]).w;
                            const uint32_t g2 = ld_pkt4(&scr->LP[b][lh][2][0]).w, g3 = ld_pkt4(&scr->LP[b][lh][3][0]).w;
                            if ((g0 == rtag) & (g1 == rtag) & (g2 == rtag) & (g3 == rtag)) break;
                            pause_cycles(200); spin_check(n2);
                        }
                    } else {
                        while (ld_pkt4(&scr->P[63][s][0][0]).w != tag) spin_check(n2);
                    }
                }
                asm volatile("bar.sync %0, 256;" ::"r"(2 + grp) : "memory");
                const uint4* lp = &scr->LP[b][lh == NLATE - 1 ? lh + (s % NREP) : lh][0][p];
                uint4 a[4];
                bool okq[4] = {false, false, false, false};
                unsigned n = 0;
                while (true) {
#pragma unroll
                    for (int q = 0; q < 4; q++) { if (!okq[q]) a[q] = ld_pkt4(lp + q * 256); }
#pragma unroll
                    for (int q = 0; q < 4; q++) okq[q] = a[q].w == rtag;
                    if (okq[0] && okq[1] && okq[2] && okq[3]) break;
                    spin_check(n);
                }
                e0 += (__uint_as_float(a[0].x) + __uint_as_float(a[1].x)) + (__uint_as_float(a[2].x) + __uint_as_float(a[3].x));
                e1 += (__uint_as_float(a[0].y) + __uint_as_float(a[1].y)) + (__uint_as_float(a[2].y) + __uint_as_float(a[3].y));
                e2 += (__uint_as_float(a[0].z) + __uint_as_float(a[1].z)) + (__uint_as_float(a[2].z) + __uint_as_float(a[3].z));
            }
            if (grp) {
                lates[p] = e0; lates[p + 256] = e1;
                if (p < 128) lates[p + 512] = e2;
                asm volatile("bar.arrive 4, 512;" ::: "memory");
            } else {
                const float x0 = xs[b * 640 + p], x1 = xs[b * 640 + p + 256], x2 = p < 128 ? xs[b * 640 + p + 512] : 0.f;
                const float y0 = early[p], y1 = early[p + 256], y2 = p < 128 ? early[p + 512] : 0.f;
                asm volatile("bar.sync 4, 512;" ::: "memory");
                v0 = bf16r(x0 + bf16r((y0 + lates[p]) + e0));
                v1 = bf16r(x1 + bf16r((y1 + lates[p + 256]) + e1));
                hs[p] = v0; hs[p + 256] = v1;
                if (p < 128) { v2 = bf16r(x2 + bf16r((y2 + lates[p + 512]) + e2)); hs[p + 512] = v2; }
            }
            if (tid == 0) TS(3);
            block_ln(smem, grp == 0, v0, v1, v2);
            if (tid == 0) TS(16);
        }
        {
            float a4[4] = {0, 0, 0, 0}, b4[4] = {0, 0, 0, 0};
            const int mt = warp & 1, kg = warp >> 1;
            uint32_t bf[10];
#pragma unroll
            for (int i = 0; i < 5; i++) { const int ks = kg * 5 + i; bf[2 * i] = actw[8 * ks + c]; bf[2 * i + 1] = actw[8 * ks + 4 + c]; }
#pragma unroll
            for (int i = 0; i < 5; i++) {
                if (i & 1) mma16816(b4, w1f[i][0], w1f[i][1], w1f[i][2], w1f[i][3], bf[2 * i], bf[2 * i + 1]);
                else mma16816(a4, w1f[i][0], w1f[i][1], w1f[i][2], w1f[i][3], bf[2 * i], bf[2 * i + 1]);
            }
            if (c == 0) { red[kg * 32 + 16 * mt + g] = a4[0] + b4[0]; red[kg * 32 + 16 * mt + g + 8] = a4[2] + b4[2]; }
            __syncthreads();
            if (tid == 0) TS(17);
            if (tid < 32) {
                float a = 0.f, a2 = 0.f;
#pragma unroll
                for (int k = 0; k < 8; k += 2) { a += red[k * 32 + tid]; a2 += red[(k + 1) * 32 + tid]; }
                reinterpret_cast<__nv_bfloat16*>(smem + SV_O)[tid] = __float2bfloat16_rn(fmaxf(bf16r(a + a2), 0.f));
            }
            __syncthreads();
        }
        if (tid == 0) TS(18);
        {
            const uint32_t* hw = reinterpret_cast<const uint32_t*>(smem + SV_O);
            const uint32_t b0 = hw[c], b1 = hw[4 + c], b2 = hw[8 + c], b3 = hw[12 + c];
            float o4[3][4];
#pragma unroll
            for (int i = 0; i < 3; i++) {
                o4[i][0] = o4[i][1] = o4[i][2] = o4[i][3] = 0.f;
                mma16816(o4[i], w2f[i][0], w2f[i][1], w2f[i][2], w2f[i][3], b0, b1);
            }
#pragma unroll
            for (int i = 0; i < 3; i++) mma16816(o4[i], w2f[3 + i][0], w2f[3 + i][1], w2f[3 + i][2], w2f[3 + i][3], b2, b3);
            publish640(scr->OP[s], o4, rtag);
        }
        if (tid == 0) TS(4);
        if (s < NRED) {
            gather8<NFFN>(smem, &scr->OP[min(tid >> 3, NFFN - 1)][8 * s + (tid & 7)], rtag);
            if (tid < 24) {
                const int n = 8 * s + (tid & 7) + 256 * (tid >> 3);
                float y = 0.f, y2 = 0.f;
#pragma unroll
                for (int w = 0; w < 12; w += 2) { y += red[w * 24 + tid]; y2 += red[(w + 1) * 24 + tid]; }
                if (n < 640) outp[b * 640 + n] = __float2bfloat16_rn(hs[n] + bf16r(y + y2));
            }
            if (tid == 0) TS(5);
        }
        __syncthreads();
    }
    if (s == 0 && tid == 0) scr->epoch[0] = epoch + 1;
}

__global__ void __launch_bounds__(NTHREADS, 1)
fused_decode_kernel(const __grid_constant__ CUtensorMap mk, const __grid_constant__ CUtensorMap mv,
                    const __grid_constant__ CUtensorMap mq, const __grid_constant__ CUtensorMap mo,
                    const __grid_constant__ CUtensorMap m1, const __grid_constant__ CUtensorMap m2, const Params prm) {
    extern __shared__ uint8_t smem_raw[];
    uint8_t* smem = smem_raw + ((1024u - (smem_u32(smem_raw) & 1023u)) & 1023u);
    const int role = blockIdx.x & 1, idx = blockIdx.x >> 1;
    const unsigned long long t_start = globaltimer();
    Scratch* scr = &g_scr;
    __nv_bfloat16* outp = prm.out;
    asm volatile("" : "+l"(scr), "+l"(outp));
    const unsigned epoch = ld_relaxed_u32(&scr->epoch[0]);
    uint32_t xr0 = 0, xr1 = 0, xr2 = 0;
    if (role == 1) {
        const unsigned short* xp = reinterpret_cast<const unsigned short*>(prm.x) + (threadIdx.x >> 8) * 640 + (threadIdx.x & 255);
        xr0 = xp[0]; xr1 = xp[256];
        if ((threadIdx.x & 255) < 128) xr2 = xp[512];
    }
    const uint32_t sbase = smem_u32(smem);
    if (role == 0) {
        const int t = threadIdx.x;
        if (t == 0) { TS(0); TSCAL(0); prefetch_map(&mk); prefetch_map(&mv); }
        if (t < 4 * NI + 2 * NSC) mbar_init(sbase + ST_BAR + 8 * t, t < 2 * NI ? 1 : 4);
        if (t >= 64 && t < 64 + NBH) mbar_init(sbase + ST_QBAR + 8 * (t - 64), 1);
        if (t < 128) {
            asm volatile("fence.mbarrier_init.release.cluster;" ::: "memory");
            asm volatile("fence.proxy.async.shared::cta;" ::: "memory");
        }
    } else if (threadIdx.x == 0) {
        TS(0); TSCAL(0);
        for (int i = 0; i < 6; i++) mbar_init(sbase + SV_BAR + 8 * i, 1);
        asm volatile("fence.mbarrier_init.release.cluster;" ::: "memory");
        asm volatile("fence.proxy.async.shared::cta;" ::: "memory");
#pragma unroll 1
        for (int rc = 0; rc < 4; rc++) {
            mbar_expect_tx(sbase + SV_BAR + 8 * rc, 3 * 160 * 64);
#pragma unroll 1
            for (int cb = 0; cb < 3; cb++) tma2d(sbase + SV_R1 + cb * 40960 + rc * 10240, &mq, 96 * idx + 32 * cb, 160 * rc, sbase + SV_BAR + 8 * rc);
        }
        if (idx < NFFN) {
            mbar_expect_tx(sbase + SV_BAR + 40, 81920);
#pragma unroll 1
            for (int rc = 0; rc < 4; rc++) tma2d(sbase + SV_W1 + rc * 10240, &m1, 32 * idx, 160 * rc, sbase + SV_BAR + 40);
#pragma unroll 1
            for (int nb = 0; nb < 10; nb++) tma2d(sbase + SV_W2 + nb * 4096, &m2, 64 * nb, 32 * idx, sbase + SV_BAR + 40);
        }
        prefetch_map(&mo);
    }
    __syncthreads();
    if (role == 0) streamer(smem, scr, &mk, &mv, idx, epoch, t_start);
    else service(smem, scr, outp, &mo, idx, epoch, xr0, xr1, xr2);
    if (threadIdx.x == 0) TSCAL(1);
}

typedef CUresult (*EncodeFn)(CUtensorMap*, CUtensorMapDataType, cuuint32_t, void*, const cuuint64_t*, const cuuint64_t*,
                             const cuuint32_t*, const cuuint32_t*, CUtensorMapInterleave, CUtensorMapSwizzle,
                             CUtensorMapL2promotion, CUtensorMapFloatOOBfill);

bool make_map(EncodeFn enc, CUtensorMap* m, const void* p, uint64_t cols, uint64_t rows, uint32_t box_c, uint32_t box_r, CUtensorMapSwizzle sw) {
    cuuint64_t dims[2] = {cols, rows};
    cuuint64_t strides[1] = {cols * 2};
    cuuint32_t box[2] = {box_c, box_r};
    cuuint32_t es[2] = {1, 1};
    return enc(m, CU_TENSOR_MAP_DATA_TYPE_BFLOAT16, 2, const_cast<void*>(p), dims, strides, box, es, CU_TENSOR_MAP_INTERLEAVE_NONE, sw,
               CU_TENSOR_MAP_L2_PROMOTION_L2_128B, CU_TENSOR_MAP_FLOAT_OOB_FILL_NONE) == CUDA_SUCCESS;
}

}

extern "C" void kernel_launch(void* const* d_in, const int* in_sizes, int n_in, void* d_out, int out_size) {
    (void)in_sizes; (void)n_in; (void)out_size;
    static EncodeFn enc = nullptr;
    if (!enc) {
        void* fn = nullptr;
        cudaDriverEntryPointQueryResult qr;
        if (cudaGetDriverEntryPoint("cuTensorMapEncodeTiled", &fn, cudaEnableDefault, &qr) != cudaSuccess || !fn) return;
        enc = (EncodeFn)fn;
        cudaFuncSetAttribute(fused_decode_kernel, cudaFuncAttributeMaxDynamicSharedMemorySize, SMEM_BYTES);
    }
    CUtensorMap mk, mv, mq, mo, m1, m2;
    bool ok = true;
    ok &= make_map(enc, &mk, d_in[1], 64, (uint64_t)NBH * SK * 3, 64, KEYS * 3, CU_TENSOR_MAP_SWIZZLE_128B);
    ok &= make_map(enc, &mv, d_in[2], 64, (uint64_t)NBH * SK * 3, 64, KEYS * 3, CU_TENSOR_MAP_SWIZZLE_128B);
    ok &= make_map(enc, &mq, d_in[3], NH * DH, DM, 32, 160, CU_TENSOR_MAP_SWIZZLE_64B);
    ok &= make_map(enc, &mo, d_in[4], DM, NH * DH, 64, 48, CU_TENSOR_MAP_SWIZZLE_128B);
    ok &= make_map(enc, &m1, d_in[6], DFF, DM, 32, 160, CU_TENSOR_MAP_SWIZZLE_64B);
    ok &= make_map(enc, &m2, d_in[7], DM, DFF, 64, 32, CU_TENSOR_MAP_SWIZZLE_128B);
    if (!ok) return;
    Params prm;
    prm.x = (const __nv_bfloat16*)d_in[0];
    prm.out = (__nv_bfloat16*)d_out;
    fused_decode_kernel<<<2 * NSTR, NTHREADS, SMEM_BYTES, cudaStreamPerThread>>>(mk, mv, mq, mo, m1, m2, prm);
}
```

```cpp
#include <cuda_runtime.h>
#include <cuda_bf16.h>
#include <cuda.h>
#include <stdint.h>

namespace {

constexpr int DM = 640, NH = 32, SK = 16384, DH = 192, DFF = 1536, NBH = 64;
constexpr int KEYS = 64;
constexpr int IPB = SK / KEYS;
constexpr int NITEMS = NBH * IPB;
constexpr int NSTR = 64, NSVC = 64;
constexpr int KV_DELAY_CYC = 1000;
constexpr int FIRST_ITEMS = 2;
constexpr int POLL_PAUSE = 600;
constexpr int DONE_PAUSE = 2000;
constexpr int W12_DELAY = 3500;
constexpr int FINAL0_PAUSE = 2000;
constexpr int NS = 5;
constexpr int NI = NS / 2;
constexpr int TILE_BYTES = KEYS * DH * 2;
constexpr int NTHREADS = 512;
constexpr int NDYN = NITEMS - NI * NSTR;
constexpr unsigned TICKETS_PER_LAUNCH = NDYN + NSTR;
constexpr int PQ = 18;
constexpr int NFFN = 48;
constexpr int NRED = 32;
constexpr float LOG2E = 1.4426950408889634f;
constexpr float SCALE = 0.07216878364870322f;
constexpr uint32_t DESC_END = 0x7fffu;

constexpr int ST_RING = 0;
constexpr int ST_Q = NS * TILE_BYTES;
constexpr int NSC = 2;
constexpr int ST_SC = ST_Q + NBH * DH * 2;
constexpr int SC_STRIDE = 72;
constexpr int ST_BAR = ST_SC + NSC * SC_STRIDE * 4;
constexpr int ST_DESC = ST_BAR + (2 * NS + 2 * NSC) * 8;
constexpr int ST_QBAR = ST_DESC + 64;
constexpr int ST_END = ST_QBAR + NBH * 8;
constexpr int SV_R1 = 0;
constexpr int SV_W1 = 122880;
constexpr int SV_W2 = SV_W1 + 40960;
constexpr int SV_ACT = SV_W2 + 40960;
constexpr int ACT_STRIDE = 648;
constexpr int SV_X = SV_ACT + 2 * ACT_STRIDE * 2;
constexpr int SV_H = SV_X + 1280 * 4;
constexpr int SV_H0 = SV_H + 640 * 4;
constexpr int SV_EARLY = SV_H0 + 640 * 4;
constexpr int SV_LATE = SV_EARLY + 640 * 4;
constexpr int SV_RED = SV_LATE + 640 * 4;
constexpr int SV_O = SV_RED + (16 * 48 + 32) * 4;
constexpr int SV_LN = SV_O + 256;
constexpr int SV_BAR = SV_LN + 128;
constexpr int SV_END = SV_BAR + 8 * 8;
constexpr int SMEM_BYTES = (ST_END > SV_END ? ST_END : SV_END) + 16 + 1024;
static_assert(SMEM_BYTES <= 232448, "smem");

struct Params {
    const __nv_bfloat16* x;
    __nv_bfloat16* out;
};

constexpr int NLATE = 4;
struct Scratch {
    unsigned epoch[32];
    unsigned ticket[32];
    unsigned done[NBH * 4];
    unsigned long long Q[NBH * 96];
    uint4 ES[256];
    uint4 H0[256];
    uint4 LP[2][NLATE][4][256];
    uint4 OP[NFFN][2][256];
    uint4 EP[NSVC + 16][256];
    uint4 P[NBH][NSTR][4][PQ];
};
__device__ __align__(128) Scratch g_scr;

__device__ __forceinline__ uint32_t smem_u32(const void* p) { return (uint32_t)__cvta_generic_to_shared(p); }
__device__ __forceinline__ void mbar_init(uint32_t bar, uint32_t cnt) { asm volatile("mbarrier.init.shared::cta.b64 [%0], %1;" ::"r"(bar), "r"(cnt)); }
__device__ __forceinline__ void mbar_expect_tx(uint32_t bar, uint32_t bytes) { asm volatile("mbarrier.arrive.expect_tx.shared::cta.b64 _, [%0], %1;" ::"r"(bar), "r"(bytes) : "memory"); }
__device__ __forceinline__ void mbar_arrive(uint32_t bar) { asm volatile("mbarrier.arrive.shared::cta.b64 _, [%0];" ::"r"(bar) : "memory"); }
__device__ __forceinline__ bool mbar_try(uint32_t bar, uint32_t parity) {
    uint32_t ok;
    asm volatile("{\n.reg .pred p;\nmbarrier.try_wait.parity.shared::cta.b64 p, [%1], %2;\nselp.u32 %0, 1, 0, p;\n}" : "=r"(ok) : "r"(bar), "r"(parity) : "memory");
    return ok != 0;
}
constexpr unsigned SPIN_LIMIT = 1u << 24;
__device__ __forceinline__ void mbar_wait(uint32_t bar, uint32_t parity) {
    unsigned n = 0;
    while (!mbar_try(bar, parity)) { if (++n > SPIN_LIMIT) __trap(); }
}
__device__ __forceinline__ void tma2d(uint32_t dst, const CUtensorMap* map, int c0, int c1, uint32_t bar) {
    asm volatile("cp.async.bulk.tensor.2d.shared::cluster.global.mbarrier::complete_tx::bytes [%0], [%1, {%3, %4}], [%2];"
                 ::"r"(dst), "l"(map), "r"(bar), "r"(c0), "r"(c1) : "memory");
}
__device__ __forceinline__ void tma2d_hint(uint32_t dst, const CUtensorMap* map, int c0, int c1, uint32_t bar, uint64_t pol) {
    asm volatile("cp.async.bulk.tensor.2d.shared::cluster.global.mbarrier::complete_tx::bytes.L2::cache_hint [%0], [%1, {%3, %4}], [%2], %5;"
                 ::"r"(dst), "l"(map), "r"(bar), "r"(c0), "r"(c1), "l"(pol) : "memory");
}
__device__ __forceinline__ void prefetch_map(const CUtensorMap* map) { asm volatile("prefetch.tensormap [%0];" ::"l"(map) : "memory"); }
__device__ __forceinline__ void ldsm4(uint32_t addr, uint32_t& r0, uint32_t& r1, uint32_t& r2, uint32_t& r3) {
    asm volatile("ldmatrix.sync.aligned.m8n8.x4.shared.b16 {%0,%1,%2,%3}, [%4];" : "=r"(r0), "=r"(r1), "=r"(r2), "=r"(r3) : "r"(addr));
}
__device__ __forceinline__ void ldsm4t(uint32_t addr, uint32_t& r0, uint32_t& r1, uint32_t& r2, uint32_t& r3) {
    asm volatile("ldmatrix.sync.aligned.m8n8.x4.trans.shared.b16 {%0,%1,%2,%3}, [%4];" : "=r"(r0), "=r"(r1), "=r"(r2), "=r"(r3) : "r"(addr));
}
__device__ __forceinline__ void mma16816(float (&d)[4], uint32_t a0, uint32_t a1, uint32_t a2, uint32_t a3, uint32_t b0, uint32_t b1) {
    asm volatile("mma.sync.aligned.m16n8k16.row.col.f32.bf16.bf16.f32 {%0,%1,%2,%3}, {%4,%5,%6,%7}, {%8,%9}, {%0,%1,%2,%3};"
                 : "+f"(d[0]), "+f"(d[1]), "+f"(d[2]), "+f"(d[3]) : "r"(a0), "r"(a1), "r"(a2), "r"(a3), "r"(b0), "r"(b1));
}
__device__ __forceinline__ float ex2(float x) { float y; asm("ex2.approx.ftz.f32 %0, %1;" : "=f"(y) : "f"(x)); return y; }
__device__ __forceinline__ uint32_t pack_bf16(float lo, float hi) {
    uint32_t r; asm("cvt.rn.bf16x2.f32 %0, %1, %2;" : "=r"(r) : "f"(hi), "f"(lo)); return r;
}
__device__ __forceinline__ float bf16r(float x) { return __uint_as_float(pack_bf16(0.f, x) & 0xffff0000u); }
__device__ __forceinline__ void st_pkt(unsigned long long* p, uint32_t payload, uint32_t tag) {
    unsigned long long v = ((unsigned long long)tag << 32) | payload;
    asm volatile("st.relaxed.gpu.global.b64 [%0], %1;" ::"l"(p), "l"(v) : "memory");
}
__device__ __forceinline__ unsigned long long ld_pkt(const unsigned long long* p) {
    unsigned long long v; asm volatile("ld.relaxed.gpu.global.b64 %0, [%1];" : "=l"(v) : "l"(p) : "memory"); return v;
}
__device__ __forceinline__ uint32_t pkt_tag(unsigned long long v) { return (uint32_t)(v >> 32); }
__device__ __forceinline__ void st_pkt4(uint4* p, uint32_t a, uint32_t b, uint32_t c, uint32_t tag) {
    asm volatile("{\n.reg .b64 lo, hi;\n.reg .b128 t;\nmov.b64 lo, {%1, %2};\nmov.b64 hi, {%3, %4};\nmov.b128 t, {lo, hi};\nst.relaxed.gpu.global.b128 [%0], t;\n}"
                 ::"l"(p), "r"(a), "r"(b), "r"(c), "r"(tag) : "memory");
}
__device__ __forceinline__ void st_pkt4f(uint4* p, float a, float b, float c, uint32_t tag) { st_pkt4(p, __float_as_uint(a), __float_as_uint(b), __float_as_uint(c), tag); }
__device__ __forceinline__ uint4 ld_pkt4(const uint4* p) {
    uint4 v;
    asm volatile("{\n.reg .b64 lo, hi;\n.reg .b128 t;\nld.relaxed.gpu.global.b128 t, [%4];\nmov.b128 {lo, hi}, t;\nmov.b64 {%0, %1}, lo;\nmov.b64 {%2, %3}, hi;\n}"
                 : "=r"(v.x), "=r"(v.y), "=r"(v.z), "=r"(v.w) : "l"(p) : "memory");
    return v;
}
__device__ __forceinline__ unsigned ld_relaxed_u32(const unsigned* p) {
    unsigned v; asm volatile("ld.relaxed.gpu.global.u32 %0, [%1];" : "=r"(v) : "l"(p) : "memory"); return v;
}
__device__ __forceinline__ void pause_cycles(int cyc) {
    const long long t0 = clock64();
    while (clock64() - t0 < cyc) {}
}
__device__ __forceinline__ void red_add_u32(unsigned* p, unsigned v) { asm volatile("red.relaxed.gpu.global.add.u32 [%0], %1;" ::"l"(p), "r"(v) : "memory"); }
__device__ __forceinline__ void spin_check(unsigned& n) { if (++n > SPIN_LIMIT) __trap(); }
__device__ __forceinline__ uint4 poll_pkt4(const uint4* p, uint32_t tag) {
    uint4 v; unsigned n = 0;
    while (true) { v = ld_pkt4(p); if (v.w == tag) break; spin_check(n); }
    return v;
}
__device__ __forceinline__ int opaque(int v) { asm volatile("" : "+r"(v)); return v; }

__device__ __forceinline__ void streamer(uint8_t* smem, Scratch* scr, const CUtensorMap* mk, const CUtensorMap* mv, int j, unsigned epoch, long long t_start) {
    const int warp = threadIdx.x >> 5, lane = threadIdx.x & 31;
    const uint32_t sbase = smem_u32(smem);
    const uint32_t bar0 = sbase + ST_BAR;
    volatile uint32_t* desc = reinterpret_cast<volatile uint32_t*>(smem + ST_DESC);
    auto full = [&](int s) { return bar0 + 8 * s; };
    auto empty = [&](int s) { return bar0 + 8 * (NS + s); };
    auto adv = [&](int& s, uint32_t& ph) { if (++s == NS) { s = 0; ph ^= 1; } };
    static_assert(!(NS & 1) || (NS + 1) / 2 >= NSC + 1, "ring / score buffer depths");
    const uint32_t tag = 2 * epoch + 1;

    auto scFull = [&](int b) { return bar0 + 8 * (2 * NS + b); };
    auto scEmpty = [&](int b) { return bar0 + 8 * (2 * NS + NSC + b); };
    float* sc = reinterpret_cast<float*>(smem + ST_SC);
    const int g = lane >> 2, c = lane & 3, mat = lane >> 3, r8 = lane & 7;

    if (warp == 8) {
        if (lane == 0) {
            uint64_t pol;
            asm volatile("createpolicy.fractional.L2::evict_first.b64 %0, 1.0;" : "=l"(pol));
            int s = 0; uint32_t ph = 1;
            auto issue = [&](unsigned item) {
                mbar_wait(empty(s), ph);
                desc[s] = item;
                mbar_expect_tx(full(s), TILE_BYTES);
                tma2d_hint(sbase + ST_RING + s * TILE_BYTES, mk, 0, (int)item * (KEYS * 3), full(s), pol);
                adv(s, ph);
                mbar_wait(empty(s), ph);
                mbar_expect_tx(full(s), TILE_BYTES);
                tma2d_hint(sbase + ST_RING + s * TILE_BYTES, mv, 0, (int)item * (KEYS * 3), full(s), pol);
                adv(s, ph);
            };
            while (clock64() - t_start < KV_DELAY_CYC) {}
#pragma unroll 1
            for (int i = 0; i < FIRST_ITEMS; i++) issue(j + NSTR * i);
            unsigned d0 = atomicAdd(&scr->ticket[0], 1u);
            mbar_wait(sbase + ST_QBAR, 0);
#pragma unroll 1
            for (int i = FIRST_ITEMS; i < NI; i++) issue(j + NSTR * i);
            const unsigned base = epoch * TICKETS_PER_LAUNCH;
            while (true) {
                const unsigned c0 = d0 - base;
                if (c0 >= (unsigned)NDYN) break;
                d0 = atomicAdd(&scr->ticket[0], 1u);
                issue(c0 + NI * NSTR);
            }
            mbar_wait(empty(s), ph);
            desc[s] = DESC_END;
            mbar_arrive(full(s));
        }
    } else if (warp == 9) {
        uint32_t* qs = reinterpret_cast<uint32_t*>(smem + ST_Q);
        for (int bh = 0; bh < NBH; bh++) {
            unsigned long long v0, v1, v2; unsigned n = 0;
            while (true) {
                v0 = ld_pkt(&scr->Q[bh * 96 + lane]); v1 = ld_pkt(&scr->Q[bh * 96 + 32 + lane]); v2 = ld_pkt(&scr->Q[bh * 96 + 64 + lane]);
                bool ok = pkt_tag(v0) == tag && pkt_tag(v1) == tag && pkt_tag(v2) == tag;
                if (__all_sync(0xffffffffu, ok)) break;
                spin_check(n);
            }
            qs[bh * 96 + lane] = (uint32_t)v0; qs[bh * 96 + 32 + lane] = (uint32_t)v1; qs[bh * 96 + 64 + lane] = (uint32_t)v2;
            __syncwarp();
            if (lane == 0) mbar_arrive(sbase + ST_QBAR + 8 * bh);
        }
    } else if (warp >= 4 && warp < 8) {
        const int w4 = warp - 4;
        uint32_t koff[3];
        {
            int key = 16 * w4 + (mat & 1) * 8 + r8;
#pragma unroll
            for (int sg = 0; sg < 3; sg++) { int row = 3 * key + sg; koff[sg] = row * 128 + (((mat >> 1) ^ (row & 7)) << 4); }
        }
        const uint32_t* qs = reinterpret_cast<const uint32_t*>(smem + ST_Q);
        uint32_t qa[24];
        int cur_bh = -1;
        int s = 0; uint32_t ph = 0; int par = 0; uint32_t sph = 1;
        bool dry = opaque(1) != 0;
        while (true) {
            uint32_t d = 0;
            if (!dry) { mbar_wait(scEmpty(par), sph); mbar_wait(full(s), ph); d = desc[s]; }
            float* scb = sc + par * SC_STRIDE;
            if (d == DESC_END) {
                if (lane == 0) { if (w4 == 0) reinterpret_cast<uint32_t*>(scb)[64] = d; mbar_arrive(scFull(par)); }
                break;
            }
            const int bh = (d & 0x7fffu) / IPB;
            if (bh != cur_bh) {
                cur_bh = bh;
                if (!dry) mbar_wait(sbase + ST_QBAR + 8 * bh, 0);
#pragma unroll
                for (int jj = 0; jj < 12; jj++) { qa[2 * jj] = qs[bh * 96 + 8 * jj + c]; qa[2 * jj + 1] = qs[bh * 96 + 8 * jj + 4 + c]; }
            }
            const uint32_t kb = sbase + ST_RING + s * TILE_BYTES;
            float sa[3][4];
            {
                uint32_t kf[12][4];
#pragma unroll
                for (int jj = 0; jj < 12; jj++) ldsm4(kb + (koff[jj >> 2] ^ ((jj & 3) << 5)), kf[jj][0], kf[jj][1], kf[jj][2], kf[jj][3]);
#pragma unroll
                for (int sg = 0; sg < 3; sg++) { sa[sg][0] = sa[sg][1] = sa[sg][2] = sa[sg][3] = 0.f; }
#pragma unroll
                for (int i = 0; i < 4; i++)
#pragma unroll
                    for (int sg = 0; sg < 3; sg++) {
                        const int jj = 4 * sg + i;
                        mma16816(sa[sg], kf[jj][0], kf[jj][1], kf[jj][2], kf[jj][3], qa[2 * jj], qa[2 * jj + 1]);
                    }
            }
            const float r0 = (sa[0][0] + sa[1][0]) + sa[2][0], r1 = (sa[0][2] + sa[1][2]) + sa[2][2];
            const float v = bf16r(bf16r(c == 0 ? r0 : r1) * SCALE);
            __syncwarp();
            if (dry) { dry = false; cur_bh = -1; continue; }
            if (lane == 0) mbar_arrive(empty(s));
            if (c < 2) scb[16 * w4 + g + 8 * c] = v;
            if (w4 == 0 && lane == 2) reinterpret_cast<uint32_t*>(scb)[64] = d;
            __syncwarp();
            if (lane == 0) mbar_arrive(scFull(par));
            if (++par == NSC) { par = 0; sph ^= 1; }
            adv(s, ph); adv(s, ph);
        }
    } else if (warp < 4) {
        uint32_t voff[3];
        {
            int key = (mat >> 1) * 8 + r8;
#pragma unroll
            for (int t = 0; t < 3; t++) { int cj = 6 * warp + 2 * t + (mat & 1); int row = 3 * key + (cj >> 3); voff[t] = row * 128 + (((cj & 7) ^ (row & 7)) << 4); }
        }
        float o[3][4];
#pragma unroll
        for (int t = 0; t < 3; t++) { o[t][0] = o[t][1] = o[t][2] = o[t][3] = 0.f; }
        if (c < 2 || (c == 2 && g < 2)) {
            st_pkt4(scr->P[NBH - 1][j][warp] + (c < 2 ? 2 + 8 * c + g : g), 0u, 0u, 0u, 0u);
            st_pkt4(scr->P[NBH - 2][j][warp] + (c < 2 ? 2 + 8 * c + g : g), 0u, 0u, 0u, 0u);
        }
        float m = -INFINITY, l = 0.f, lt = 0.f;
        int cur_bh = 0, nit = 0;
        int s = 1; uint32_t ph = 0; int par = 0; uint32_t sph = 0;
        bool dry = opaque(1) != 0;
        while (true) {
            const float* scb = sc + par * SC_STRIDE;
            if (!dry) mbar_wait(scFull(par), sph);
            const float2 sv = *reinterpret_cast<const float2*>(scb + 2 * lane);
            uint32_t d = reinterpret_cast<const uint32_t*>(scb)[64];
            if (dry) d = IPB;
            __syncwarp();
            if (lane == 0 && !dry) mbar_arrive(scEmpty(par));
            const int bh = d == DESC_END ? NBH : (int)(d / IPB);
            if (bh != cur_bh) {
                if (!dry) {
                    uint4* P = scr->P[cur_bh][j][warp];
                    const uint32_t pa = c < 2 ? __float_as_uint(c == 1 ? o[0][2] : o[0][0]) : ((__float_as_uint(m) & 0xffff0000u) | (uint32_t)nit);
                    const uint32_t pb2 = c < 2 ? __float_as_uint(c == 1 ? o[1][2] : o[1][0]) : __float_as_uint(lt);
                    const uint32_t pc = __float_as_uint(c == 1 ? o[2][2] : o[2][0]);
                    if (c < 2 || (c == 2 && g < 2)) st_pkt4(P + (c < 2 ? 2 + 8 * c + g : g), pa, pb2, pc, tag);
                    if (lane == 0) red_add_u32(&scr->done[cur_bh * 4 + warp], (unsigned)nit);
#pragma unroll 1
                    for (int e = cur_bh + 1; e < bh; e++)
                        if (c == 2 && g < 2) st_pkt4(scr->P[e][j][warp] + g, 0xff800000u, 0u, 0u, tag);
                }
                if (d == DESC_END) break;
                cur_bh = bh; nit = 0; m = -INFINITY; l = 0.f;
#pragma unroll
                for (int t = 0; t < 3; t++) { o[t][0] = o[t][1] = o[t][2] = o[t][3] = 0.f; }
            }
            nit++;
            int key = __float_as_int(fmaxf(sv.x, sv.y));
            key ^= (key >> 31) & 0x7fffffff;
            key = __reduce_max_sync(0xffffffffu, key);
            key ^= (key >> 31) & 0x7fffffff;
            const float mn = fmaxf(m, __int_as_float(key));
            const float ms = mn == -INFINITY ? 0.f : mn;
            const float mb = ms * LOG2E;
            const float p0 = ex2(fmaf(sv.x, LOG2E, -mb)), p1 = ex2(fmaf(sv.y, LOG2E, -mb));
            const float alpha = ex2((m - ms) * LOG2E);
            m = mn;
            const uint32_t pk = pack_bf16(p0, p1);
            uint32_t pb[8];
#pragma unroll
            for (int i = 0; i < 8; i++) pb[i] = __shfl_sync(0xffffffffu, pk, 4 * i + c);
            l = fmaf(l, alpha, p0 + p1);
            lt = l;
#pragma unroll
            for (int off = 1; off < 32; off <<= 1) lt += __shfl_xor_sync(0xffffffffu, lt, off);
#pragma unroll
            for (int t = 0; t < 3; t++) { o[t][0] *= alpha; o[t][2] *= alpha; }
            if (!dry) mbar_wait(full(s), ph);
            const uint32_t vb = sbase + ST_RING + s * TILE_BYTES;
            {
                uint32_t vf[12][4];
#pragma unroll
                for (int kk = 0; kk < 4; kk++)
#pragma unroll
                    for (int t = 0; t < 3; t++) ldsm4t(vb + voff[t] + kk * 6144, vf[3 * kk + t][0], vf[3 * kk + t][1], vf[3 * kk + t][2], vf[3 * kk + t][3]);
#pragma unroll
                for (int kk = 0; kk < 4; kk++)
#pragma unroll
                    for (int t = 0; t < 3; t++) mma16816(o[t], vf[3 * kk + t][0], vf[3 * kk + t][1], vf[3 * kk + t][2], vf[3 * kk + t][3], pb[2 * kk], pb[2 * kk + 1]);
            }
            __syncwarp();
            if (dry) {
                dry = false; cur_bh = 0; nit = 0; m = -INFINITY; l = 0.f;
#pragma unroll
                for (int t = 0; t < 3; t++) { o[t][0] = o[t][1] = o[t][2] = o[t][3] = 0.f; }
                continue;
            }
            if (lane == 0) mbar_arrive(empty(s));
            if (++par == NSC) { par = 0; sph ^= 1; }
            adv(s, ph); adv(s, ph);
        }
    }
}

__device__ __forceinline__ void block_ln(uint8_t* smem, bool active, int row, float v0, float v1, float v2) {
    const int tid = threadIdx.x, warp = tid >> 5, lane = tid & 31;
    const int grp = warp >> 3, w8 = warp & 7, p = tid & 255;
    const bool has3 = w8 < 4;
    float* lnb = reinterpret_cast<float*>(smem + SV_LN) + grp * 16;
    if (active) {
        float mean = has3 ? ((v0 + v1) + v2) * (1.f / 3.f) : (v0 + v1) * 0.5f;
        const float d0 = v0 - mean, d1 = v1 - mean, d2 = has3 ? v2 - mean : 0.f;
        float m2 = d0 * d0 + d1 * d1 + d2 * d2;
        float cnt_half = has3 ? 1.5f : 1.f;
#pragma unroll
        for (int off = 1; off < 32; off <<= 1) {
            const float mo = __shfl_xor_sync(0xffffffffu, mean, off), m2o = __shfl_xor_sync(0xffffffffu, m2, off);
            const float dl = mo - mean;
            m2 = m2 + m2o + dl * dl * cnt_half;
            mean = 0.5f * (mean + mo);
            cnt_half *= 2.f;
        }
        if (lane == 0) *reinterpret_cast<float2*>(lnb + w8 * 2) = make_float2(mean, m2);
    }
    __syncthreads();
    if (active) {
        const float4 a = *reinterpret_cast<const float4*>(lnb), b = *reinterpret_cast<const float4*>(lnb + 4);
        const float4 c = *reinterpret_cast<const float4*>(lnb + 8), d = *reinterpret_cast<const float4*>(lnb + 12);
        const float mean = ((a.x + a.z) + (b.x + b.z)) * 0.15f + ((c.x + c.z) + (d.x + d.z)) * 0.1f;
        const float e0 = a.x - mean, e1 = a.z - mean, e2 = b.x - mean, e3 = b.z - mean, e4 = c.x - mean, e5 = c.z - mean, e6 = d.x - mean, e7 = d.z - mean;
        const float m2 = ((a.y + a.w) + (b.y + b.w)) + ((c.y + c.w) + (d.y + d.w)) + 96.f * ((e0 * e0 + e1 * e1) + (e2 * e2 + e3 * e3)) + 64.f * ((e4 * e4 + e5 * e5) + (e6 * e6 + e7 * e7));
        const float mr = bf16r(mean), vr = bf16r(m2 * (1.f / 640.f));
        const float den = bf16r(__fsqrt_rn(bf16r(vr + 1e-5f)));
        __nv_bfloat16* act = reinterpret_cast<__nv_bfloat16*>(smem + SV_ACT) + row * ACT_STRIDE;
        act[p] = __float2bfloat16_rn(__fdividef(bf16r(v0 - mr), den));
        act[p + 256] = __float2bfloat16_rn(__fdividef(bf16r(v1 - mr), den));
        if (has3) act[p + 512] = __float2bfloat16_rn(__fdividef(bf16r(v2 - mr), den));
    }
    __syncthreads();
}

__device__ __forceinline__ void combine(uint8_t* smem, const Scratch* scr, int bh, int qt, uint32_t tag) {
    const int tid = threadIdx.x, warp = tid >> 5, lane = tid & 31;
    const int jrow = 4 * warp + (lane >> 3), pg = lane & 7;
    const uint4* rp = scr->P[bh][jrow][qt];
    uint4 hd = make_uint4(0, 0, 0, 0), d0 = hd, d1 = hd;
    bool nonempty = false, ok = false;
    unsigned n = 0;
    while (true) {
        if (!ok) {
            hd = ld_pkt4(rp); d0 = ld_pkt4(rp + 2 + pg); d1 = ld_pkt4(rp + 10 + pg);
            nonempty = (hd.x & 0xffffu) != 0;
            ok = hd.w == tag && (!nonempty || (d0.w == tag && d1.w == tag));
        }
        if (__all_sync(0xffffffffu, ok)) break;
        spin_check(n);
    }
    const float mj = __uint_as_float(hd.x & 0xffff0000u);
    float M = mj;
    M = fmaxf(M, __shfl_xor_sync(0xffffffffu, M, 8));
    M = fmaxf(M, __shfl_xor_sync(0xffffffffu, M, 16));
    nonempty = nonempty && mj != -INFINITY;
    const float wj = nonempty ? ex2((mj - M) * LOG2E) : 0.f;
    float val[7];
    val[0] = nonempty ? __uint_as_float(d0.x) * wj : 0.f; val[1] = nonempty ? __uint_as_float(d0.y) * wj : 0.f; val[2] = nonempty ? __uint_as_float(d0.z) * wj : 0.f;
    val[3] = nonempty ? __uint_as_float(d1.x) * wj : 0.f; val[4] = nonempty ? __uint_as_float(d1.y) * wj : 0.f; val[5] = nonempty ? __uint_as_float(d1.z) * wj : 0.f;
    val[6] = nonempty ? __uint_as_float(hd.y) * wj : 0.f;
#pragma unroll
    for (int i = 0; i < 7; i++) { val[i] += __shfl_xor_sync(0xffffffffu, val[i], 8); val[i] += __shfl_xor_sync(0xffffffffu, val[i], 16); }
    float* red = reinterpret_cast<float*>(smem + SV_RED);
    if (lane < 8) {
#pragma unroll
        for (int i = 0; i < 3; i++) { red[warp * 48 + 16 * i + pg] = val[i]; red[warp * 48 + 16 * i + 8 + pg] = val[3 + i]; }
        if (lane == 0) { red[768 + warp] = M; red[784 + warp] = val[6]; }
    }
    __syncthreads();
    if (tid < 64) {
        const float Mw = red[768 + (lane & 15)];
        int key = __float_as_int(Mw);
        key ^= (key >> 31) & 0x7fffffff;
        key = __reduce_max_sync(0xffffffffu, key);
        key ^= (key >> 31) & 0x7fffffff;
        const float scw = Mw == -INFINITY ? 0.f : ex2((Mw - __int_as_float(key)) * LOG2E);
        const int dd = tid < 48 ? tid : 0;
        float a0 = 0.f, a1 = 0.f, l0 = 0.f, l1 = 0.f;
#pragma unroll
        for (int w = 0; w < 16; w += 2) {
            const float s0 = __shfl_sync(0xffffffffu, scw, w), s1 = __shfl_sync(0xffffffffu, scw, w + 1);
            a0 = fmaf(s0, red[w * 48 + dd], a0); a1 = fmaf(s1, red[(w + 1) * 48 + dd], a1);
            l0 = fmaf(s0, red[784 + w], l0); l1 = fmaf(s1, red[784 + w + 1], l1);
        }
        if (tid < 48) reinterpret_cast<__nv_bfloat16*>(smem + SV_O)[tid] = __float2bfloat16_rn(__fdividef(a0 + a1, l0 + l1));
    }
    __syncthreads();
}

__device__ __forceinline__ void wo_load(uint8_t* smem, int slice, uint32_t (&af)[9][4]) {
    const int warp = threadIdx.x >> 5, lane = threadIdx.x & 31;
    const int mat = lane >> 3, r8 = lane & 7;
    const uint32_t base = smem_u32(smem) + SV_R1 + slice * 61440;
#pragma unroll
    for (int kk = 0; kk < 3; kk++) {
        const int row = 16 * kk + (mat >> 1) * 8 + r8;
#pragma unroll
        for (int i = 0; i < 3; i++) {
            const int t = min(warp + 16 * i, 39);
            ldsm4t(base + (t >> 2) * 6144 + row * 128 + (((((t & 3) << 1) + (mat & 1)) ^ (row & 7)) << 4), af[3 * kk + i][0], af[3 * kk + i][1], af[3 * kk + i][2], af[3 * kk + i][3]);
        }
    }
}
__device__ __forceinline__ void wo_mma(uint8_t* smem, const uint32_t (&af)[9][4], float (&acc)[3][4]) {
    const int c = threadIdx.x & 3;
    const uint32_t* ow = reinterpret_cast<const uint32_t*>(smem + SV_O);
    uint32_t bf[6];
#pragma unroll
    for (int kk = 0; kk < 3; kk++) { bf[2 * kk] = ow[8 * kk + c]; bf[2 * kk + 1] = ow[8 * kk + 4 + c]; }
#pragma unroll
    for (int kk = 0; kk < 3; kk++)
#pragma unroll
        for (int i = 0; i < 3; i++) mma16816(acc[i], af[3 * kk + i][0], af[3 * kk + i][1], af[3 * kk + i][2], af[3 * kk + i][3], bf[2 * kk], bf[2 * kk + 1]);
}
__device__ __forceinline__ uint4* slot640(uint4* base) {
    const int warp = threadIdx.x >> 5, lane = threadIdx.x & 31, g = lane >> 2, c = lane & 3;
    uint4* p = base + 16 * warp + 8 * (c & 1) + g;
    asm volatile("" : "+l"(p));
    return p;
}
__device__ __forceinline__ void publish640(uint4* slot, const float (&acc)[3][4], uint32_t tag) {
    const int c = threadIdx.x & 3;
    if (c < 2) st_pkt4f(slot, c ? acc[0][2] : acc[0][0], c ? acc[1][2] : acc[1][0], c ? acc[2][2] : acc[2][0], tag);
}

template <int NPROD>
__device__ __forceinline__ void gather8(uint8_t* smem, const uint4* src, uint32_t tag) {
    const int tid = threadIdx.x, warp = tid >> 5, lane = tid & 31;
    float x0 = 0.f, x1 = 0.f, x2 = 0.f;
    if (tid < NPROD * 8) {
        uint4 v; unsigned n = 0;
        while (true) { v = ld_pkt4(src); if (v.w == tag) break; spin_check(n); }
        x0 = __uint_as_float(v.x); x1 = __uint_as_float(v.y); x2 = __uint_as_float(v.z);
    }
    x0 += __shfl_xor_sync(0xffffffffu, x0, 8); x1 += __shfl_xor_sync(0xffffffffu, x1, 8); x2 += __shfl_xor_sync(0xffffffffu, x2, 8);
    x0 += __shfl_xor_sync(0xffffffffu, x0, 16); x1 += __shfl_xor_sync(0xffffffffu, x1, 16); x2 += __shfl_xor_sync(0xffffffffu, x2, 16);
    float* red = reinterpret_cast<float*>(smem + SV_RED);
    if (lane < 8) { red[warp * 24 + lane] = x0; red[warp * 24 + 8 + lane] = x1; red[warp * 24 + 16 + lane] = x2; }
    __syncthreads();
}

__device__ __forceinline__ void final_reduce(uint8_t* smem, const Scratch* scr, const float* h, __nv_bfloat16* outp, int bb, int r, uint32_t tag, bool dry) {
    const int tid = threadIdx.x, warp = tid >> 5, lane = tid & 31;
    float* red = reinterpret_cast<float*>(smem + SV_RED);
    float x0 = 0.f, x1 = 0.f, x2 = 0.f;
    if (tid < NFFN * 8 && !dry) {
        const uint4* src = &scr->OP[tid >> 3][bb][8 * r + (tid & 7)];
        const uint4 v = poll_pkt4(src, tag);
        x0 = __uint_as_float(v.x); x1 = __uint_as_float(v.y); x2 = __uint_as_float(v.z);
    }
    x0 += __shfl_xor_sync(0xffffffffu, x0, 8); x1 += __shfl_xor_sync(0xffffffffu, x1, 8); x2 += __shfl_xor_sync(0xffffffffu, x2, 8);
    x0 += __shfl_xor_sync(0xffffffffu, x0, 16); x1 += __shfl_xor_sync(0xffffffffu, x1, 16); x2 += __shfl_xor_sync(0xffffffffu, x2, 16);
    if (lane < 8) { red[warp * 24 + lane] = x0; red[warp * 24 + 8 + lane] = x1; red[warp * 24 + 16 + lane] = x2; }
    __syncthreads();
    if (tid < 24) {
        const int n = 8 * r + (tid & 7) + 256 * (tid >> 3);
        float y = 0.f, y2 = 0.f;
#pragma unroll
        for (int w = 0; w < 12; w += 2) { y += red[w * 24 + tid]; y2 += red[(w + 1) * 24 + tid]; }
        if (n < 640 && !dry) outp[bb * 640 + n] = __float2bfloat16_rn(h[n] + bf16r(y + y2));
    }
}

__device__ __forceinline__ void service(uint8_t* smem, Scratch* scr, __nv_bfloat16* outp, const CUtensorMap* mo, const CUtensorMap* m1, const CUtensorMap* m2, int s, unsigned epoch) {
    const int tid = threadIdx.x, warp = tid >> 5, lane = tid & 31;
    const int g = lane >> 2, c = lane & 3, mat = lane >> 3, r8 = lane & 7;
    const uint32_t sbase = smem_u32(smem);
    const uint32_t bar_wq = sbase + SV_BAR, bar_wo = bar_wq + 32, bar_w12 = bar_wq + 40;
    const uint32_t tag = 2 * epoch + 1;
    float* xs = reinterpret_cast<float*>(smem + SV_X);
    float* hs = reinterpret_cast<float*>(smem + SV_H);
    float* h0s = reinterpret_cast<float*>(smem + SV_H0);
    float* early = reinterpret_cast<float*>(smem + SV_EARLY);
    float* lates = reinterpret_cast<float*>(smem + SV_LATE);
    float* red = reinterpret_cast<float*>(smem + SV_RED);
    const uint32_t* actw = reinterpret_cast<const uint32_t*>(smem + SV_ACT);
    const int h0 = s >> 2, qt = s & 3;
    const bool late_owner = (h0 >= 16 - NLATE);

    auto load_w12 = [&]() {
        mbar_expect_tx(bar_w12, 81920);
#pragma unroll 1
        for (int rc = 0; rc < 4; rc++) tma2d(sbase + SV_W1 + rc * 10240, m1, 32 * s, 160 * rc, bar_w12);
#pragma unroll 1
        for (int nb = 0; nb < 10; nb++) tma2d(sbase + SV_W2 + nb * 4096, m2, 64 * nb, 32 * s, bar_w12);
    };
    {
        const int b = tid >> 8, p = tid & 255;
        const unsigned short* xb = reinterpret_cast<const unsigned short*>(smem + SV_LATE) + b * 640 + p;
        const float v0 = __uint_as_float((uint32_t)xb[0] << 16), v1 = __uint_as_float((uint32_t)xb[256] << 16);
        const float v2 = p < 128 ? __uint_as_float((uint32_t)xb[512] << 16) : 0.f;
        xs[b * 640 + p] = v0; xs[b * 640 + p + 256] = v1;
        if (p < 128) xs[b * 640 + p + 512] = v2;
        block_ln(smem, true, tid >> 8, v0, v1, v2);
    }
    {
        float acc[4] = {0, 0, 0, 0};
        const int mt = warp % 6, kp = warp / 6;
        if (warp < 12) {
#pragma unroll 1
            for (int rc = 0; rc < 4; rc++) {
                mbar_wait(bar_wq + 8 * rc, 0);
#pragma unroll
                for (int i = 0; i < 5; i++) {
                    const int ks = rc * 10 + 2 * i + kp;
                    const int row = 16 * ks + (mat >> 1) * 8 + r8;
                    const int ch = ((mt & 1) << 1) + (mat & 1);
                    uint32_t a0, a1, a2, a3;
                    ldsm4t(sbase + SV_R1 + (mt >> 1) * 40960 + row * 64 + ((ch ^ ((row >> 1) & 3)) << 4), a0, a1, a2, a3);
                    const uint32_t b0 = actw[(g & 1) * (ACT_STRIDE / 2) + 8 * ks + c], b1 = actw[(g & 1) * (ACT_STRIDE / 2) + 8 * ks + 4 + c];
                    mma16816(acc, a0, a1, a2, a3, b0, b1);
                }
            }
            if (c == 0) {
                *reinterpret_cast<float2*>(red + (kp * 96 + 16 * mt + g) * 2) = make_float2(acc[0], acc[1]);
                *reinterpret_cast<float2*>(red + (kp * 96 + 16 * mt + g + 8) * 2) = make_float2(acc[2], acc[3]);
            }
        }
        __syncthreads();
        if (tid < 96) {
            const int b = tid / 48, pi = tid % 48;
            const float q0 = red[(2 * pi) * 2 + b] + red[(96 + 2 * pi) * 2 + b];
            const float q1 = red[(2 * pi + 1) * 2 + b] + red[(96 + 2 * pi + 1) * 2 + b];
            st_pkt(&scr->Q[(b * 32 + (s >> 1)) * 96 + (s & 1) * 48 + pi], pack_bf16(q0, q1), tag);
        }
        if (tid == 128) {
            asm volatile("fence.proxy.async.shared::cta;" ::: "memory");
            mbar_expect_tx(bar_wo, 122880);
#pragma unroll 1
            for (int i = 0; i < 20; i++) {
                const int sl = i / 10, nb = i % 10;
                tma2d(sbase + SV_R1 + sl * 61440 + nb * 6144, mo, 64 * nb, (h0 + 16 * sl) * DH + qt * 48, bar_wo);
            }
        }
        __syncthreads();
    }
    const unsigned tbase = epoch * TICKETS_PER_LAUNCH;
    auto wait_handed_out = [&](int bh) {
        if (tid == 0) {
            const int need = (bh + 1) * IPB - NI * NSTR;
            unsigned n = 0;
            while ((int)(ld_relaxed_u32(&scr->ticket[0]) - tbase) < need) { pause_cycles(POLL_PAUSE); spin_check(n); }
        }
        __syncthreads();
    };
    mbar_wait(bar_wo, 0);

#pragma unroll 1
    for (int b = 0; b < 2; b++) {
        const uint32_t rtag = tag + b;
        float acc[3][4];
#pragma unroll
        for (int i = 0; i < 3; i++) acc[i][0] = acc[i][1] = acc[i][2] = acc[i][3] = 0.f;
        uint4* const out_slot = slot640(late_owner ? scr->LP[b][h0 - (16 - NLATE)][qt] : scr->EP[s]);
#pragma unroll 1
        for (int task = 0; task < 2; task++) {
            const int bh = 32 * b + h0 + 16 * task;
            if (task == 1 && late_owner) {
                publish640(slot640(scr->EP[b == 0 ? s : s + 16]), acc, rtag);
#pragma unroll
                for (int i = 0; i < 3; i++) acc[i][0] = acc[i][1] = acc[i][2] = acc[i][3] = 0.f;
            }
            uint32_t af[9][4];
            wo_load(smem, task, af);
            if (bh < 62) {
                if (tid == 0) {
                    const unsigned target = (epoch + 1) * IPB;
                    unsigned n = 0;
                    while ((int)(ld_relaxed_u32(&scr->done[bh * 4 + qt]) - target) < 0) { pause_cycles(POLL_PAUSE); spin_check(n); }
                    pause_cycles(DONE_PAUSE);
                }
                __syncthreads();
            } else {
                wait_handed_out(bh);
            }
            combine(smem, scr, bh, qt, tag);
            wo_mma(smem, af, acc);
        }
        if (late_owner) {
            publish640(out_slot, acc, rtag);
            if (b == 0 && c < 2) st_pkt4(slot640(scr->LP[1][h0 - (16 - NLATE)][qt]), 0u, 0u, 0u, 0u);
            if (b == 1) {
                if (tid < 256) {
                    uint4 v; unsigned n = 0;
                    while (true) { v = ld_pkt4(&scr->H0[tid]); if (v.w == tag) break; spin_check(n); }
                    hs[tid] = __uint_as_float(v.x); hs[tid + 256] = __uint_as_float(v.y);
                    if (tid < 128) hs[tid + 512] = __uint_as_float(v.z);
                }
                if (tid == 0) {
                    unsigned n2 = 0;
                    while (ld_pkt4(&scr->LP[1][NLATE - 1][0][0]).w != rtag) spin_check(n2);
                    pause_cycles(FINAL0_PAUSE);
                }
                __syncthreads();
                final_reduce(smem, scr, hs, outp, 0, s - 32, rtag, false);
            }
            continue;
        }
        publish640(out_slot, acc, rtag);
        wait_handed_out(32 * b + 32 - NLATE);
        if (s < NRED) {
            const int prod = tid >> 3;
            gather8<NSVC>(smem, &scr->EP[(prod >= NFFN && b == 1) ? prod + 16 : prod][8 * s + (tid & 7)], rtag);
            if (tid < 8) {
                float y0 = 0.f, y1 = 0.f, y2 = 0.f;
#pragma unroll
                for (int w = 0; w < 16; w++) { y0 += red[w * 24 + tid]; y1 += red[w * 24 + 8 + tid]; y2 += red[w * 24 + 16 + tid]; }
                st_pkt4f(&scr->ES[8 * s + tid], y0, y1, y2, rtag);
            }
        }
        if (tid < 256) {
            uint4 v; unsigned n = 0;
            while (true) { v = ld_pkt4(&scr->ES[tid]); if (v.w == rtag) break; spin_check(n); pause_cycles(100); }
            early[tid] = __uint_as_float(v.x); early[tid + 256] = __uint_as_float(v.y);
            if (tid < 128) early[tid + 512] = __uint_as_float(v.z);
        }
        const bool dry = (b == 0);
        const int grp = warp >> 3, p = tid & 255;
        float e0 = 0.f, e1 = 0.f, e2 = 0.f;
        auto collect = [&](int lh) {
            const uint4* lp = &scr->LP[b][lh][0][p];
            uint4 a[4];
            bool okq[4] = {false, false, false, false};
            unsigned n = 0;
            while (true) {
#pragma unroll
                for (int q = 0; q < 4; q++) { if (!okq[q]) a[q] = ld_pkt4(lp + q * 256); }
#pragma unroll
                for (int q = 0; q < 4; q++) okq[q] = a[q].w == rtag;
                if (okq[0] && okq[1] && okq[2] && okq[3]) break;
                spin_check(n);
            }
            e0 += (__uint_as_float(a[0].x) + __uint_as_float(a[1].x)) + (__uint_as_float(a[2].x) + __uint_as_float(a[3].x));
            e1 += (__uint_as_float(a[0].y) + __uint_as_float(a[1].y)) + (__uint_as_float(a[2].y) + __uint_as_float(a[3].y));
            e2 += (__uint_as_float(a[0].z) + __uint_as_float(a[1].z)) + (__uint_as_float(a[2].z) + __uint_as_float(a[3].z));
        };
        auto gate = [&](int lh) {
            unsigned n2 = 0;
            while (true) {
                const uint32_t g0 = ld_pkt4(&scr->LP[b][lh][0][0]).w, g1 = ld_pkt4(&scr->LP[b][lh][1][0]).w;
                const uint32_t g2 = ld_pkt4(&scr->LP[b][lh][2][0]).w, g3 = ld_pkt4(&scr->LP[b][lh][3][0]).w;
                if ((g0 == rtag) & (g1 == rtag) & (g2 == rtag) & (g3 == rtag)) break;
                pause_cycles(200); spin_check(n2);
            }
        };
        if (grp) {
#pragma unroll 1
            for (int lh = 0; lh < NLATE - 1; lh++) {
                if (p == 0) gate(lh);
                asm volatile("bar.sync 3, 256;" ::: "memory");
                collect(lh);
            }
            lates[p] = e0; lates[p + 256] = e1;
            if (p < 128) lates[p + 512] = e2;
        } else if (p == 0) {
            if (b == 0) gate(NLATE - 1);
            else {
                unsigned n2 = 0;
                while ((int)(ld_relaxed_u32(&scr->ticket[0]) - tbase) < NDYN) { pause_cycles(200); spin_check(n2); }
                pause_cycles(W12_DELAY);
                load_w12();
            }
        }
        uint32_t w1f[5][4], w2f[6][4];
        {
            if (!dry) mbar_wait(bar_w12, 0);
            else __syncthreads();
            const int mt = warp & 1, kg = warp >> 1;
#pragma unroll
            for (int i = 0; i < 5; i++) {
                const int row = 16 * (kg * 5 + i) + (mat >> 1) * 8 + r8;
                const int ch = (mt << 1) + (mat & 1);
                ldsm4t(sbase + SV_W1 + row * 64 + ((ch ^ ((row >> 1) & 3)) << 4), w1f[i][0], w1f[i][1], w1f[i][2], w1f[i][3]);
            }
#pragma unroll
            for (int kk = 0; kk < 2; kk++) {
                const int row = 16 * kk + (mat >> 1) * 8 + r8;
#pragma unroll
                for (int i = 0; i < 3; i++) {
                    const int t = min(warp + 16 * i, 39);
                    ldsm4t(sbase + SV_W2 + (t >> 2) * 4096 + row * 128 + (((((t & 3) << 1) + (mat & 1)) ^ (row & 7)) << 4), w2f[3 * kk + i][0], w2f[3 * kk + i][1], w2f[3 * kk + i][2], w2f[3 * kk + i][3]);
                }
            }
        }
        uint4* op_slot = &scr->OP[s][c & 1][16 * warp + 8 * (c >> 1) + g];
        asm volatile("" : "+l"(op_slot));
        {
            float v0 = 0.f, v1 = 0.f, v2 = 0.f;
            if (grp == 0) {
                const float x0 = xs[b * 640 + p], x1 = xs[b * 640 + p + 256], x2 = p < 128 ? xs[b * 640 + p + 512] : 0.f;
                const float y0 = early[p], y1 = early[p + 256], y2 = p < 128 ? early[p + 512] : 0.f;
                e0 = e1 = e2 = 0.f;
                collect(NLATE - 1);
                asm volatile("bar.sync 4, 512;" ::: "memory");
                v0 = bf16r(x0 + bf16r((y0 + lates[p]) + e0));
                v1 = bf16r(x1 + bf16r((y1 + lates[p + 256]) + e1));
                if (p < 128) v2 = bf16r(x2 + bf16r((y2 + lates[p + 512]) + e2));
                hs[p] = v0; hs[p + 256] = v1;
                if (p < 128) hs[p + 512] = v2;
                if (b == 0) {
                    h0s[p] = v0; h0s[p + 256] = v1;
                    if (p < 128) h0s[p + 512] = v2;
                    if (s == 0) st_pkt4f(&scr->H0[p], v0, v1, v2, tag);
                }
            } else {
                asm volatile("bar.arrive 4, 512;" ::: "memory");
            }
            block_ln(smem, grp == 0, b, v0, v1, v2);
        }
        {
            float a4[4] = {0, 0, 0, 0}, b4[4] = {0, 0, 0, 0};
            const int mt = warp & 1, kg = warp >> 1;
            const uint32_t* ar = actw + (g & 1) * (ACT_STRIDE / 2);
            uint32_t bf[10];
#pragma unroll
            for (int i = 0; i < 5; i++) { const int ks = kg * 5 + i; bf[2 * i] = ar[8 * ks + c]; bf[2 * i + 1] = ar[8 * ks + 4 + c]; }
#pragma unroll
            for (int i = 0; i < 5; i++) {
                if (i & 1) mma16816(b4, w1f[i][0], w1f[i][1], w1f[i][2], w1f[i][3], bf[2 * i], bf[2 * i + 1]);
                else mma16816(a4, w1f[i][0], w1f[i][1], w1f[i][2], w1f[i][3], bf[2 * i], bf[2 * i + 1]);
            }
            if (c == 0) {
                *reinterpret_cast<float2*>(red + (kg * 32 + 16 * mt + g) * 2) = make_float2(a4[0] + b4[0], a4[1] + b4[1]);
                *reinterpret_cast<float2*>(red + (kg * 32 + 16 * mt + g + 8) * 2) = make_float2(a4[2] + b4[2], a4[3] + b4[3]);
            }
            __syncthreads();
            if (tid < 64) {
                const int f = tid >> 1, bb = tid & 1;
                float a = 0.f, a2 = 0.f;
#pragma unroll
                for (int k = 0; k < 8; k += 2) { a += red[(k * 32 + f) * 2 + bb]; a2 += red[((k + 1) * 32 + f) * 2 + bb]; }
                reinterpret_cast<__nv_bfloat16*>(smem + SV_O)[bb * 40 + f] = __float2bfloat16_rn(fmaxf(bf16r(a + a2), 0.f));
            }
            __syncthreads();
        }
        {
            const uint32_t* hw = reinterpret_cast<const uint32_t*>(smem + SV_O) + (g & 1) * 20;
            const uint32_t b0 = hw[c], b1 = hw[4 + c], b2 = hw[8 + c], b3 = hw[12 + c];
            float o4[3][4];
#pragma unroll
            for (int i = 0; i < 3; i++) {
                o4[i][0] = o4[i][1] = o4[i][2] = o4[i][3] = 0.f;
                mma16816(o4[i], w2f[i][0], w2f[i][1], w2f[i][2], w2f[i][3], b0, b1);
            }
#pragma unroll
            for (int i = 0; i < 3; i++) mma16816(o4[i], w2f[3 + i][0], w2f[3 + i][1], w2f[3 + i][2], w2f[3 + i][3], b2, b3);
            const float y0 = c == 0 ? o4[0][0] : (c == 1 ? o4[0][1] : (c == 2 ? o4[0][2] : o4[0][3]));
            const float y1 = c == 0 ? o4[1][0] : (c == 1 ? o4[1][1] : (c == 2 ? o4[1][2] : o4[1][3]));
            const float y2 = c == 0 ? o4[2][0] : (c == 1 ? o4[2][1] : (c == 2 ? o4[2][2] : o4[2][3]));
            st_pkt4f(op_slot, y0, y1, y2, dry ? 0u : rtag);
        }
        final_reduce(smem, scr, s < NRED ? hs : h0s, outp, s < NRED ? 1 : 0, s < NRED ? s : s - 32, rtag, dry);
        __syncthreads();
    }
    if (s == 0 && tid == 0) scr->epoch[0] = epoch + 1;
}

__global__ void __launch_bounds__(NTHREADS, 1)
fused_decode_kernel(const __grid_constant__ CUtensorMap mk, const __grid_constant__ CUtensorMap mv,
                    const __grid_constant__ CUtensorMap mq, const __grid_constant__ CUtensorMap mo,
                    const __grid_constant__ CUtensorMap m1, const __grid_constant__ CUtensorMap m2, const Params prm) {
    extern __shared__ uint8_t smem_raw[];
    uint8_t* smem = smem_raw + ((1024u - (smem_u32(smem_raw) & 1023u)) & 1023u);
    const int role = blockIdx.x & 1, idx = blockIdx.x >> 1;
    const long long t_start = clock64();
    if (threadIdx.x == 0) { if (role == 1) prefetch_map(&mq); else { prefetch_map(&mk); prefetch_map(&mv); } }
    uint4 xv[5];
    if (role == 1 && threadIdx.x < 32) {
#pragma unroll
        for (int i = 0; i < 5; i++) xv[i] = reinterpret_cast<const uint4*>(prm.x)[threadIdx.x + 32 * i];
    }
    Scratch* scr = &g_scr;
    unsigned epoch0 = 0;
    if (threadIdx.x == 0) epoch0 = ld_relaxed_u32(&scr->epoch[0]);
    __nv_bfloat16* outp = prm.out;
    asm volatile("" : "+l"(scr), "+l"(outp));
    const uint32_t sbase = smem_u32(smem);
    if (role == 0) {
        const int t = threadIdx.x;
        if (t < 2 * NS + 2 * NSC) mbar_init(sbase + ST_BAR + 8 * t, t < NS ? 1 : 4);
        if (t >= 64 && t < 64 + NBH) mbar_init(sbase + ST_QBAR + 8 * (t - 64), 1);
        if (t < 128) {
            asm volatile("fence.mbarrier_init.release.cluster;" ::: "memory");
            asm volatile("fence.proxy.async.shared::cta;" ::: "memory");
        }
    } else if (threadIdx.x == 0) {
        for (int i = 0; i < 6; i++) mbar_init(sbase + SV_BAR + 8 * i, 1);
        asm volatile("fence.mbarrier_init.release.cluster;" ::: "memory");
        asm volatile("fence.proxy.async.shared::cta;" ::: "memory");
#pragma unroll 1
        for (int rc = 0; rc < 4; rc++) {
            mbar_expect_tx(sbase + SV_BAR + 8 * rc, 3 * 160 * 64);
#pragma unroll 1
            for (int cb = 0; cb < 3; cb++) tma2d(sbase + SV_R1 + cb * 40960 + rc * 10240, &mq, 96 * idx + 32 * cb, 160 * rc, sbase + SV_BAR + 8 * rc);
        }
        prefetch_map(&m1); prefetch_map(&m2);
        prefetch_map(&mo);
    }
    volatile unsigned* s_epoch = reinterpret_cast<volatile unsigned*>(smem + (role == 0 ? ST_END : SV_END));
    if (role == 1 && threadIdx.x < 32) {
#pragma unroll
        for (int i = 0; i < 5; i++) reinterpret_cast<uint4*>(smem + SV_LATE)[threadIdx.x + 32 * i] = xv[i];
    }
    if (threadIdx.x == 0) *s_epoch = epoch0;
    __syncthreads();
    const unsigned epoch = *s_epoch;
    if (role == 0) streamer(smem, scr, &mk, &mv, idx, epoch, t_start);
    else service(smem, scr, outp, &mo, &m1, &m2, idx, epoch);
}

typedef CUresult (*EncodeFn)(CUtensorMap*, CUtensorMapDataType, cuuint32_t, void*, const cuuint64_t*, const cuuint64_t*,
                             const cuuint32_t*, const cuuint32_t*, CUtensorMapInterleave, CUtensorMapSwizzle,
                             CUtensorMapL2promotion, CUtensorMapFloatOOBfill);

bool make_map(EncodeFn enc, CUtensorMap* m, const void* p, uint64_t cols, uint64_t rows, uint32_t box_c, uint32_t box_r, CUtensorMapSwizzle sw) {
    cuuint64_t dims[2] = {cols, rows};
    cuuint64_t strides[1] = {cols * 2};
    cuuint32_t box[2] = {box_c, box_r};
    cuuint32_t es[2] = {1, 1};
    return enc(m, CU_TENSOR_MAP_DATA_TYPE_BFLOAT16, 2, const_cast<void*>(p), dims, strides, box, es, CU_TENSOR_MAP_INTERLEAVE_NONE, sw,
               CU_TENSOR_MAP_L2_PROMOTION_L2_128B, CU_TENSOR_MAP_FLOAT_OOB_FILL_NONE) == CUDA_SUCCESS;
}

}

extern "C" void kernel_launch(void* const* d_in, const int* in_sizes, int n_in, void* d_out, int out_size) {
    (void)in_sizes; (void)n_in; (void)out_size;
    static EncodeFn enc = nullptr;
    if (!enc) {
        void* fn = nullptr;
        cudaDriverEntryPointQueryResult qr;
        if (cudaGetDriverEntryPoint("cuTensorMapEncodeTiled", &fn, cudaEnableDefault, &qr) != cudaSuccess || !fn) return;
        enc = (EncodeFn)fn;
        cudaFuncSetAttribute(fused_decode_kernel, cudaFuncAttributeMaxDynamicSharedMemorySize, SMEM_BYTES);
    }
    CUtensorMap mk, mv, mq, mo, m1, m2;
    bool ok = true;
    ok &= make_map(enc, &mk, d_in[1], 64, (uint64_t)NBH * SK * 3, 64, KEYS * 3, CU_TENSOR_MAP_SWIZZLE_128B);
    ok &= make_map(enc, &mv, d_in[2], 64, (uint64_t)NBH * SK * 3, 64, KEYS * 3, CU_TENSOR_MAP_SWIZZLE_128B);
    ok &= make_map(enc, &mq, d_in[3], NH * DH, DM, 32, 160, CU_TENSOR_MAP_SWIZZLE_64B);
    ok &= make_map(enc, &mo, d_in[4], DM, NH * DH, 64, 48, CU_TENSOR_MAP_SWIZZLE_128B);
    ok &= make_map(enc, &m1, d_in[6], DFF, DM, 32, 160, CU_TENSOR_MAP_SWIZZLE_64B);
    ok &= make_map(enc, &m2, d_in[7], DM, DFF, 64, 32, CU_TENSOR_MAP_SWIZZLE_128B);
    if (!ok) return;
    Params prm;
    prm.x = (const __nv_bfloat16*)d_in[0];
    prm.out = (__nv_bfloat16*)d_out;
    fused_decode_kernel<<<2 * NSTR, NTHREADS, SMEM_BYTES, cudaStreamPerThread>>>(mk, mv, mq, mo, m1, m2, prm);
}
```
